```python
import torch

def _softmax(x, axis=-1):
    return torch.softmax(x, dim=axis)
def _gelu(x):
    return torch.nn.functional.gelu(x, approximate="tanh")
def _silu(x):
    return torch.nn.functional.silu(x)
def _sigmoid(x):
    return torch.sigmoid(x)
def _layernorm(x, axis=-1, eps=1e-5):
    m = x.mean(dim=axis, keepdim=True)
    v = x.var(dim=axis, keepdim=True, unbiased=False)
    return (x - m) / torch.sqrt(v + eps)
def _scatter_add(tgt, idx, src, axis=0):
    return tgt.clone().index_add_(axis, idx, src)
def _segment_sum(src, seg, n):
    out = torch.zeros((n,) + src.shape[1:], dtype=src.dtype)
    return out.index_add_(0, seg, src)
def _pad(x, pw):
    flat = tuple(v for pair in reversed(pw) for v in pair)
    return torch.nn.functional.pad(x, flat)

kernel_name = 'parallel_sum__sliding_block_cached__dense_activation_gelu__decode'

def setup_inputs():

    _w = (lambda a: (lambda t: t.to(torch.bfloat16) if t.is_floating_point() else t)(torch.as_tensor(a)))
    def _A_setup():
        B, Sq, D = 2, 1, 512
        Hq, Hkv, Sk, Dh = 32, 32, 16384, 128
        assert Hq % Hkv == 0, (Hq, Hkv)
        return {
            "x": _w((lambda *s: torch.randn(*s, dtype=torch.bfloat16) * 0.05)(B, Sq, D)),
            "k_cache": _w((lambda *s: torch.randn(*s, dtype=torch.bfloat16) * 3.2)(B, Hkv, Sk, Dh)),
            "v_cache": _w((lambda *s: torch.randn(*s, dtype=torch.bfloat16) * 0.8)(B, Hkv, Sk, Dh)),
            "wq": _w((lambda *s: torch.randn(*s, dtype=torch.bfloat16) * 3.2)(D, Hq * Dh) * (D ** -0.5)),
            "wo": _w((lambda *s: torch.randn(*s, dtype=torch.bfloat16) * 0.8)(Hq * Dh, D) * ((Hq * Dh) ** -0.5)),
        }
    _A_in = _A_setup()

    def _B_setup():
        B, S, D, F = 2, 1, 512, 1376
        return {
            "x": _w((lambda *s: torch.randn(*s, dtype=torch.bfloat16) * 0.05)(B, S, D)),
            "w1": _w((lambda *s: torch.randn(*s, dtype=torch.bfloat16) * 3.2)(D, F) * (D ** -0.5)),
            "b1": _w((lambda *s: torch.randn(*s, dtype=torch.bfloat16) * 3.2)(F) * 0.01),
            "w2": _w((lambda *s: torch.randn(*s, dtype=torch.bfloat16) * 0.4)(F, D) * (F ** -0.5)),
            "b2": _w((lambda *s: torch.randn(*s, dtype=torch.bfloat16) * 0.4)(D) * 0.01),
        }
    _B_in = _B_setup()

    return {
        "A_x": _A_in["x"],
        "A_k_cache": _A_in["k_cache"],
        "A_v_cache": _A_in["v_cache"],
        "A_wq": _A_in["wq"],
        "A_wo": _A_in["wo"],
        "B_x": _B_in["x"],
        "B_w1": _B_in["w1"],
        "B_b1": _B_in["b1"],
        "B_w2": _B_in["w2"],
        "B_b2": _B_in["b2"],
    }

def reference(A_x, A_k_cache, A_v_cache, A_wq, A_wo, B_x, B_w1, B_b1, B_w2, B_b2):
    def _A_ref(x, k_cache, v_cache, wq, wo):
        B, Sq, D = x.shape
        Hq, Dh = 32, 128
        Hkv, Sk = k_cache.shape[1], k_cache.shape[2]
        W = min(4096, max(256, Sk // 4))
        rep = Hq // Hkv
        q = (lambda x, *d: x.permute(*d))((x @ wq).reshape(B, Sq, Hq, Dh), 0, 2, 1, 3)
        k = (lambda x, n, axis: torch.repeat_interleave(x, n, dim=axis))(k_cache[:, :, Sk - W:, :], rep, axis=1)
        v = (lambda x, n, axis: torch.repeat_interleave(x, n, dim=axis))(v_cache[:, :, Sk - W:, :], rep, axis=1)
        scores = torch.einsum("bhqd,bhkd->bhqk", q, k) * (Dh ** -0.5)
        p = _softmax(scores, axis=-1)
        o = torch.einsum("bhqk,bhkd->bhqd", p, v)
        return (lambda x, *d: x.permute(*d))(o, 0, 2, 1, 3).reshape(B, Sq, Hq * Dh) @ wo

    def _B_ref(x, w1, b1, w2, b2):
        h = torch.einsum("bsd,df->bsf", x, w1) + b1
        h = _gelu(h)
        return torch.einsum("bsf,fd->bsd", h, w2) + b2

    x = A_x
    xn = _layernorm(x, axis=-1)
    return x + _A_ref(xn, A_k_cache, A_v_cache, A_wq, A_wo) + _B_ref(xn, B_w1, B_b1, B_w2, B_b2)
```

```cpp
#include <cuda.h>
#include <cuda_runtime.h>
#include <cuda_bf16.h>
#include <stdint.h>

namespace {

constexpr int kD = 512, kH = 32, kDh = 128, kSk = 16384, kWin = 4096, kF = 1376;
constexpr int kAttCtas = 128, kFfnCtas = 4, kCtas = kAttCtas + kFfnCtas;
constexpr int kThreads = 320;
constexpr int kKeysPerCta = kWin / 2;
constexpr int kTileBytes = 128 * 256;
constexpr int kNT = kKeysPerCta / 128;
#define SLOTS 6
#define LIM 2
#define LIM0 2
#define LIME 4
#define NEND 4
#define WOA 8
#define WOB 8
#define KFIRST 0
#define FLIM1 3
#define FLIM2 2
constexpr int kSlots = SLOTS;
constexpr int kSlotBytes = kTileBytes + 128;
constexpr int kWoPitch = 8 * 1024 + 32;
constexpr int kChunks = 2 + 2 * kNT + 2;
constexpr int kRingBytes = kSlots * kSlotBytes;
constexpr uint32_t kEmpty = 0xFFFFFFFFu;
constexpr int kSpinMax = 1 << 22;

constexpr int kFc = kF / kFfnCtas;
constexpr int kFch = kFc / 8;

struct __align__(16) Tail {
    float part[16][128];
    uint32_t ps[8][256];
    uint32_t vec[2][68];
    float2 ml[16];
    unsigned long long full[kSlots], empty[kSlots], xq, xml, xo;
};
constexpr int kSmemBytes = kRingBytes + (int)sizeof(Tail);

__device__ unsigned long long g_arrivals;
__device__ __align__(128) uint32_t g_slots[2][64][64][8];
__device__ __align__(128) float g_ffn[kFfnCtas][2][kD];

#define STAMP(cond, i) do { } while (0)

__device__ __forceinline__ uint32_t smem_u32(const void* p) { return (uint32_t)__cvta_generic_to_shared(p); }
__device__ __forceinline__ void mbar_init(uint32_t a, uint32_t c) {
    asm volatile("mbarrier.init.shared::cta.b64 [%0], %1;" ::"r"(a), "r"(c) : "memory");
}
__device__ __forceinline__ void mbar_expect(uint32_t a, uint32_t bytes) {
    asm volatile("mbarrier.arrive.expect_tx.shared::cta.b64 _, [%0], %1;" ::"r"(a), "r"(bytes) : "memory");
}
__device__ __forceinline__ void mbar_arrive(uint32_t a) {
    asm volatile("mbarrier.arrive.shared::cta.b64 _, [%0];" ::"r"(a) : "memory");
}
__device__ __forceinline__ void mbar_wait(uint32_t a, uint32_t parity) {
    uint32_t ok;
    int it = 0;
    do {
        asm volatile("{\n.reg .pred p;\nmbarrier.try_wait.parity.shared::cta.b64 p, [%1], %2;\nselp.u32 %0, 1, 0, p;\n}"
                     : "=r"(ok) : "r"(a), "r"(parity) : "memory");
    } while (!ok && ++it < kSpinMax);
}
__device__ __forceinline__ void bulk_load(uint32_t dst, const void* src, uint32_t bytes, uint32_t bar, uint64_t pol) {
    asm volatile("cp.async.bulk.shared::cluster.global.mbarrier::complete_tx::bytes.L2::cache_hint [%0], [%1], %2, [%3], %4;"
                 ::"r"(dst), "l"(src), "r"(bytes), "r"(bar), "l"(pol) : "memory");
}
__device__ __forceinline__ void tensor_load(uint32_t dst, const CUtensorMap* map, int c0, int c1, uint32_t bar) {
    asm volatile("cp.async.bulk.tensor.2d.shared::cluster.global.mbarrier::complete_tx::bytes [%0], [%1, {%2, %3}], [%4];"
                 ::"r"(dst), "l"(map), "r"(c0), "r"(c1), "r"(bar) : "memory");
}
__device__ __forceinline__ uint32_t mapa(uint32_t a, uint32_t rank) {
    uint32_t r;
    asm("mapa.shared::cluster.u32 %0, %1, %2;" : "=r"(r) : "r"(a), "r"(rank));
    return r;
}
__device__ __forceinline__ void st_async4(uint32_t dst, float a, float b, float c, float d, uint32_t bar) {
    asm volatile("st.async.shared::cluster.mbarrier::complete_tx::bytes.v4.f32 [%0], {%1, %2, %3, %4}, [%5];"
                 ::"r"(dst), "f"(a), "f"(b), "f"(c), "f"(d), "r"(bar) : "memory");
}
__device__ __forceinline__ void st_async2(uint32_t dst, float a, float b, uint32_t bar) {
    asm volatile("st.async.shared::cluster.mbarrier::complete_tx::bytes.v2.f32 [%0], {%1, %2}, [%3];"
                 ::"r"(dst), "f"(a), "f"(b), "r"(bar) : "memory");
}
__device__ __forceinline__ uint4 lds128(uint32_t a) {
    uint4 v;
    asm volatile("ld.shared.v4.u32 {%0, %1, %2, %3}, [%4];" : "=r"(v.x), "=r"(v.y), "=r"(v.z), "=r"(v.w) : "r"(a) : "memory");
    return v;
}
__device__ __forceinline__ uint4 ld_relaxed128(const void* p) {
    uint4 v;
    asm volatile("ld.relaxed.gpu.global.v4.u32 {%0, %1, %2, %3}, [%4];"
                 : "=r"(v.x), "=r"(v.y), "=r"(v.z), "=r"(v.w) : "l"(p) : "memory");
    return v;
}
__device__ __forceinline__ void mma16816(float (&c)[4], uint32_t a0, uint32_t a1, uint32_t a2, uint32_t a3,
                                         uint32_t b0, uint32_t b1) {
    asm volatile("mma.sync.aligned.m16n8k16.row.col.f32.bf16.bf16.f32 {%0, %1, %2, %3}, {%4, %5, %6, %7}, {%8, %9}, {%0, %1, %2, %3};"
                 : "+f"(c[0]), "+f"(c[1]), "+f"(c[2]), "+f"(c[3])
                 : "r"(a0), "r"(a1), "r"(a2), "r"(a3), "r"(b0), "r"(b1));
}
__device__ __forceinline__ uint32_t bf_bits(float f) { return (uint32_t)__bfloat16_as_ushort(__float2bfloat16_rn(f)); }
__device__ __forceinline__ float bf_round(float f) { return __uint_as_float(bf_bits(f) << 16); }
__device__ __forceinline__ float bf_lo(uint32_t w) { return __uint_as_float(w << 16); }
__device__ __forceinline__ float bf_hi(uint32_t w) { return __uint_as_float(w & 0xFFFF0000u); }
__device__ __forceinline__ float warp_sum(float v) {
#pragma unroll
    for (int o = 16; o; o >>= 1) v += __shfl_xor_sync(0xFFFFFFFFu, v, o);
    return v;
}
__device__ __forceinline__ float warp_max(float v) {
#pragma unroll
    for (int o = 16; o; o >>= 1) v = fmaxf(v, __shfl_xor_sync(0xFFFFFFFFu, v, o));
    return v;
}

__device__ __forceinline__ void ln_stats(const uint4& r0, const uint4& r1, float& mean_bf, float& den_bf) {
    const uint32_t w[8] = {r0.x, r0.y, r0.z, r0.w, r1.x, r1.y, r1.z, r1.w};
    float s = 0.f;
#pragma unroll
    for (int i = 0; i < 8; i++) s += bf_lo(w[i]) + bf_hi(w[i]);
    const float mean = warp_sum(s) * (1.f / kD);
    float v = 0.f;
#pragma unroll
    for (int i = 0; i < 8; i++) {
        const float a = bf_lo(w[i]) - mean, c = bf_hi(w[i]) - mean;
        v += a * a + c * c;
    }
    const float var = warp_sum(v) * (1.f / kD);
    mean_bf = bf_round(mean);
    den_bf = bf_round(sqrtf(bf_round(bf_round(var) + 1e-5f)));
}
__device__ __forceinline__ float ln_apply(float x, float mean_bf, float den_bf) {
    return bf_round(bf_round(x - mean_bf) / den_bf);
}

__device__ __forceinline__ void fma8x2(float (&a)[2][8], const uint4& w, float2 s) {
    const uint32_t u[4] = {w.x, w.y, w.z, w.w};
#pragma unroll
    for (int i = 0; i < 4; i++) {
        const float lo = bf_lo(u[i]), hi = bf_hi(u[i]);
        a[0][2 * i] = fmaf(s.x, lo, a[0][2 * i]);
        a[0][2 * i + 1] = fmaf(s.x, hi, a[0][2 * i + 1]);
        a[1][2 * i] = fmaf(s.y, lo, a[1][2 * i]);
        a[1][2 * i + 1] = fmaf(s.y, hi, a[1][2 * i + 1]);
    }
}

constexpr int kFStages = kSlots - 1, kF1 = kD / 32, kF2 = (kFc + 31) / 32;
__device__ __forceinline__ void ffn_cta(unsigned char* smem, int f, const __nv_bfloat16* x, const CUtensorMap* w1map,
                                        const __nv_bfloat16* b1, const __nv_bfloat16* w2) {
    const uint32_t ring = smem_u32(smem);
    const uint32_t full0 = ring + kRingBytes, empty0 = full0 + 64;
    float2* xs = reinterpret_cast<float2*>(smem + kFStages * kSlotBytes);
    float2* hs = xs + kD;
    float* red = reinterpret_cast<float*>(hs + kFc + 8);
    const int tid = threadIdx.x, warp = tid >> 5, lane = tid & 31;
    if (warp == 9) return;
    if (warp == 8) {
        if (lane == 0) {
            for (int s = 0; s < kFStages; s++) { mbar_init(full0 + 8 * s, 1); mbar_init(empty0 + 8 * s, 8); }
            asm volatile("fence.mbarrier_init.release.cluster;" ::: "memory");
        }
        __syncwarp();
        asm volatile("bar.arrive 1, 288;" ::: "memory");
        if (lane == 0) {
            uint64_t pol;
            asm volatile("createpolicy.fractional.L2::evict_first.b64 %0, 1.0;" : "=l"(pol));
            int s = 0, ph = 1, landed = 0;
#pragma unroll 1
            for (int i = 0; i < kF1 + kF2; i++) {
                for (; landed <= i - (i < kF1 ? FLIM1 : FLIM2); landed++)
                    mbar_wait(full0 + 8 * (landed % kFStages), (landed / kFStages) & 1);
                mbar_wait(empty0 + 8 * s, ph);
                if (i < kF1) {
                    mbar_expect(full0 + 8 * s, 32 * kFc * 2);
                    tensor_load(ring + s * kSlotBytes, w1map, f * (kFc / 2), i * 32, full0 + 8 * s);
                } else {
                    const int r = (i - kF1) * 32;
                    const uint32_t bytes = min(32, kFc - r) * kD * 2;
                    mbar_expect(full0 + 8 * s, bytes);
                    bulk_load(ring + s * kSlotBytes, w2 + (size_t)(f * kFc + r) * kD, bytes, full0 + 8 * s, pol);
                }
                if (++s == kFStages) { s = 0; ph ^= 1; }
            }
        }
        return;
    }
    {
        const __nv_bfloat16* xb = x + (warp & 1) * kD;
        const uint4 r0 = __ldg(reinterpret_cast<const uint4*>(xb + lane * 8));
        const uint4 r1 = __ldg(reinterpret_cast<const uint4*>(xb + 256 + lane * 8));
        float mean, den;
        ln_stats(r0, r1, mean, den);
#pragma unroll 1
        for (int i = (warp >> 1) * 32 + lane; i < kD; i += 128)
            reinterpret_cast<float*>(xs)[2 * i + (warp & 1)] = ln_apply(__bfloat162float(xb[i]), mean, den);
        for (int i = tid; i < kFc; i += 256) hs[i].x = hs[i].y = __bfloat162float(b1[f * kFc + i]);
    }
    asm volatile("bar.sync 1, 288;" ::: "memory");
    STAMP(tid == 0, 1);
    int s = 0, ph = 0, c = tid % kFch, rg = tid / kFch, pitch = kFc * 2, width = kFc, rows = rg < 4 ? kD : 0;
    const float2* act = xs;
#pragma unroll 1
    for (int phase = 0; phase < 2; phase++) {
        float a[2][8] = {};
#pragma unroll 1
        for (int r = rg * 8, e = r + 32 * (phase ? kF2 : kF1); r < e; r += 32) {
            mbar_wait(full0 + 8 * s, ph);
            if (r < rows) {
#pragma unroll
                for (int u = 0; u < 8; u++)
                    fma8x2(a, lds128(ring + s * kSlotBytes + (rg * 8 + u) * pitch + c * 16), act[r + u]);
            }
            __syncwarp();
            if (lane == 0) mbar_arrive(empty0 + 8 * s);
            if (++s == kFStages) { s = 0; ph ^= 1; }
        }
        if (rg < 4) {
#pragma unroll
            for (int bb = 0; bb < 2; bb++)
#pragma unroll
                for (int i = 0; i < 8; i++) red[(rg * 2 + bb) * width + c * 8 + i] = a[bb][i];
        }
        asm volatile("bar.sync 2, 256;" ::: "memory");
        STAMP(tid == 0, 2 + phase);
#pragma unroll 1
        for (int i = tid; i < 2 * width; i += 256) {
            const float sum = (red[i] + red[2 * width + i]) + (red[4 * width + i] + red[6 * width + i]);
            if (phase) {
                (&g_ffn[f][0][0])[i] = sum;
            } else {
                float* hp = reinterpret_cast<float*>(hs) + (i < kFc ? 2 * i : 2 * (i - kFc) + 1);
                const float h = bf_round(bf_round(sum) + *hp);
                const float inner = 0.7978845608028654f * (h + 0.044715f * h * h * h);
                *hp = bf_round(0.5f * h * (1.f + tanhf(inner)));
            }
        }
        asm volatile("bar.sync 2, 256;" ::: "memory");
        c = tid & 63; rg = tid >> 6; pitch = kD * 2; width = kD; rows = kFc; act = hs;
    }
    if (tid == 0) {
        __threadfence();
        atomicAdd(&g_arrivals, 1ULL);
    }
    STAMP(tid == 0, 9);
}

__global__ void __cluster_dims__(2, 1, 1) __launch_bounds__(kThreads, 1)
fused_decode_kernel(const __grid_constant__ CUtensorMap wqmap, const __grid_constant__ CUtensorMap w1map,
                    const __nv_bfloat16* __restrict__ x, const __nv_bfloat16* __restrict__ kc,
                    const __nv_bfloat16* __restrict__ vc, const __nv_bfloat16* __restrict__ wo,
                    const __nv_bfloat16* __restrict__ b1, const __nv_bfloat16* __restrict__ w2,
                    const __nv_bfloat16* __restrict__ b2, __nv_bfloat16* __restrict__ out) {
    extern __shared__ __align__(128) unsigned char smem[];
    const int tid = threadIdx.x, warp = tid >> 5, lane = tid & 31;
    STAMP(tid == 0, 0);
    if (blockIdx.x >= kAttCtas) {
        ffn_cta(smem, blockIdx.x - kAttCtas, x, &w1map, b1, w2);
        return;
    }
    Tail* tl = reinterpret_cast<Tail*>(smem + kRingBytes);
    const uint32_t ring = smem_u32(smem);
    const uint32_t full0 = smem_u32(tl->full), empty0 = smem_u32(tl->empty);
    const uint32_t rank = blockIdx.x & 1, pair = blockIdx.x >> 1;
    const int b = pair & 1, h = pair >> 1;

    if (warp == 8) {
        const size_t off = ((size_t)(b * kH + h) * kSk + (kSk - kWin) + rank * kKeysPerCta) * (kDh * 2);
        const char* ksrc = reinterpret_cast<const char*>(kc) + off;
        const char* vsrc = reinterpret_cast<const char*>(vc) + off;
        const char* osrc = reinterpret_cast<const char*>(wo) + (size_t)(h * kDh + rank * 64) * (kD * 2);
        uint64_t pol;
        asm volatile("createpolicy.fractional.L2::evict_first.b64 %0, 1.0;" : "=l"(pol));
        if (lane == 0) {
#pragma unroll
            for (int s = 0; s < kSlots; s++) mbar_init(full0 + 8 * s, 1);
            asm volatile("fence.mbarrier_init.release.cluster;" ::: "memory");
#pragma unroll
            for (int s = 2; s < 2 + KFIRST; s++) {
                mbar_expect(full0 + 8 * s, kTileBytes);
                bulk_load(ring + s * kSlotBytes, ksrc + (s - 2) * kTileBytes, kTileBytes, full0 + 8 * s, pol);
            }
#pragma unroll
            for (int s = 0; s < 2; s++) {
                mbar_expect(full0 + 8 * s, kTileBytes);
                tensor_load(ring + s * kSlotBytes, &wqmap, h * kDh, rank * 256 + s * 128, full0 + 8 * s);
            }
#pragma unroll
            for (int s = 2 + KFIRST; s < LIM0; s++) {
                mbar_expect(full0 + 8 * s, kTileBytes);
                bulk_load(ring + s * kSlotBytes, ksrc + (s - 2) * kTileBytes, kTileBytes, full0 + 8 * s, pol);
            }
#pragma unroll
            for (int s = 0; s < kSlots; s++) mbar_init(empty0 + 8 * s, 8);
            mbar_init(smem_u32(&tl->xq), 1);
            mbar_init(smem_u32(&tl->xml), 1);
            mbar_init(smem_u32(&tl->xo), 1);
            mbar_expect(smem_u32(&tl->xq), 16 * 128 * 4);
            mbar_expect(smem_u32(&tl->xml), 16 * 8);
            mbar_expect(smem_u32(&tl->xo), 16 * 64 * 4);
            asm volatile("fence.mbarrier_init.release.cluster;" ::: "memory");
        }
        __syncwarp();
        asm volatile("barrier.cluster.arrive.relaxed.aligned;" ::: "memory");
        asm volatile("barrier.cluster.wait.aligned;" ::: "memory");
        if (lane == 0) {
            int s = LIM0 % kSlots, ph = LIM0 == kSlots ? 0 : 1;
            int landed = 0;
            const char* src = ksrc + (LIM0 - 2) * kTileBytes;
#pragma unroll 1
            for (int n = LIM0; n < kChunks; n++) {
                const int lim = n < kSlots ? LIM0 : n >= kChunks - NEND ? LIME : LIM;
                while (landed <= n - lim) {
                    const int m = landed < KFIRST ? landed + 2 : landed < KFIRST + 2 ? landed - KFIRST : landed;
                    mbar_wait(full0 + 8 * (m % kSlots), (m / kSlots) & 1);
                    landed++;
                }
                mbar_wait(empty0 + 8 * s, ph);
                mbar_expect(full0 + 8 * s, kTileBytes);
                if (n == 2 + kNT) src = vsrc;
                if (n == 2 + kNT + WOA || n == 3 + kNT + WOB) {
                    uint64_t keep;
                    asm volatile("createpolicy.fractional.L2::evict_normal.b64 %0, 1.0;" : "=l"(keep));
#pragma unroll
                    for (int u = 0; u < 4; u++)
                        bulk_load(ring + s * kSlotBytes + u * kWoPitch, osrc + u * 8192, 8192, full0 + 8 * s, keep);
                    osrc += kTileBytes;
                } else {
                    bulk_load(ring + s * kSlotBytes, src, kTileBytes, full0 + 8 * s, pol);
                    src += kTileBytes;
                }
                if (++s == kSlots) { s = 0; ph ^= 1; }
            }
            STAMP(true, 5);
        }
        return;
    }
    if (warp == 9) {
        asm volatile("barrier.cluster.arrive.relaxed.aligned;" ::: "memory");
        asm volatile("barrier.cluster.wait.aligned;" ::: "memory");
        uint32_t* region = &g_slots[b][2 * h + rank][0][0] + lane * 4;
        mbar_wait(smem_u32(&tl->xml), 0);
#pragma unroll
        for (int k = 0; k < 4; k++) *reinterpret_cast<uint4*>(region + k * 128) = make_uint4(kEmpty, kEmpty, kEmpty, kEmpty);
        __syncwarp();
        if (lane == 0) {
            __threadfence();
            const unsigned long long target = (atomicAdd(&g_arrivals, 1ULL) / kCtas + 1) * kCtas;
            unsigned long long v;
            int it = 0;
            do {
                asm volatile("ld.acquire.gpu.global.u64 %0, [%1];" : "=l"(v) : "l"(&g_arrivals) : "memory");
                if (v >= target) break;
                __nanosleep(200);
            } while (++it < kSpinMax);
            STAMP(true, 8);
        }
        __syncwarp();
        asm volatile("bar.arrive 2, 288;" ::: "memory");
        const int col = (2 * h + rank) * 8 + (lane & 1) * 4 + ((lane >> 1) & 1) * 2 + ((lane >> 2) & 1);
        const float fsum = (__ldcg(&g_ffn[0][b][col]) + __ldcg(&g_ffn[1][b][col])) +
                           (__ldcg(&g_ffn[2][b][col]) + __ldcg(&g_ffn[3][b][col]));
        const float ffn = bf_round(bf_round(fsum) + __bfloat162float(b2[col]));
        const float xv = __bfloat162float(x[b * kD + col]);
        mbar_wait(smem_u32(&tl->xo), 0);
        uint4 u[4];
        int it = 0;
        bool pending;
        do {
            pending = false;
#pragma unroll
            for (int k = 0; k < 4; k++) u[k] = ld_relaxed128(region + k * 128);
#pragma unroll
            for (int k = 0; k < 4; k++)
                pending |= u[k].x == kEmpty || u[k].y == kEmpty || u[k].z == kEmpty || u[k].w == kEmpty;
        } while (pending && ++it < kSpinMax);
        __syncwarp();
        STAMP(lane == 0, 16);
#define SUM4(c) ((__uint_as_float(u[0].c) + __uint_as_float(u[1].c)) + (__uint_as_float(u[2].c) + __uint_as_float(u[3].c)))
        const float v0 = SUM4(x), v1 = SUM4(y), v2 = SUM4(z), v3 = SUM4(w);
#undef SUM4
        const bool up = lane & 2;
        const float k0 = (up ? v2 : v0) + __shfl_xor_sync(0xFFFFFFFFu, up ? v0 : v2, 2);
        const float k1 = (up ? v3 : v1) + __shfl_xor_sync(0xFFFFFFFFu, up ? v1 : v3, 2);
        const bool up2 = lane & 4;
        float r = (up2 ? k1 : k0) + __shfl_xor_sync(0xFFFFFFFFu, up2 ? k0 : k1, 4);
        r += __shfl_xor_sync(0xFFFFFFFFu, r, 8);
        r += __shfl_xor_sync(0xFFFFFFFFu, r, 16);
        if (lane < 8) out[b * kD + col] = __float2bfloat16_rn(bf_round(xv + bf_round(r)) + ffn);
        STAMP(lane == 0, 9);
        return;
    }

    asm volatile("barrier.cluster.arrive.relaxed.aligned;" ::: "memory");
    const int g = lane >> 2, t = lane & 3;
    const uint32_t sh = (g & 1) * 16;
    int s = 0, ph = 0;
    float acc[2][2][4];
    const uint32_t mult = (g >> 1) == t ? (1u << sh) : 0u;
    const uint32_t va0 = ring + (warp * 16 + t * 4) * 256 + (g ^ (2 * t)) * 16;
    const uint32_t pa0 = smem_u32(&tl->ps[warp][t * 4]);
    auto wsum_tile = [&](int i) {
        const uint4 pw = lds128(pa0 + i * 64);
        mbar_wait(full0 + 8 * s, ph);
        uint4 v[4][2];
#pragma unroll
        for (int r = 0; r < 4; r++) {
            v[r][0] = lds128(va0 + s * kSlotBytes + r * 256);
            v[r][1] = lds128(va0 + s * kSlotBytes + r * 256 + 128);
        }
        __syncwarp();
        if (lane == 0) mbar_arrive(empty0 + 8 * s);
        const uint32_t bw[4] = {pw.x * mult, pw.y * mult, pw.z * mult, pw.w * mult};
#pragma unroll
        for (int r = 0; r < 4; r += 2)
#pragma unroll
            for (int c = 0; c < 2; c++) {
                mma16816(acc[c][0], v[r][c].x, v[r][c].y, v[r + 1][c].x, v[r + 1][c].y, bw[r], bw[r + 1]);
                mma16816(acc[c][1], v[r][c].z, v[r][c].w, v[r + 1][c].z, v[r + 1][c].w, bw[r], bw[r + 1]);
            }
        if (++s == kSlots) { s = 0; ph ^= 1; }
    };
    auto quad_reduce = [&](float (&o4)[4]) {
        float k[2][4];
#pragma unroll
        for (int j = 0; j < 2; j++)
#pragma unroll
            for (int i = 0; i < 4; i++)
                k[j][i] = ((t & 1) ? acc[1][j][i] : acc[0][j][i]) +
                          __shfl_xor_sync(0xFFFFFFFFu, (t & 1) ? acc[0][j][i] : acc[1][j][i], 9);
#pragma unroll
        for (int i = 0; i < 4; i++)
            o4[i] = ((t & 2) ? k[1][i] : k[0][i]) + __shfl_xor_sync(0xFFFFFFFFu, (t & 2) ? k[0][i] : k[1][i], 18);
    };
    const uint32_t pcol = ((g ^ (2 * t)) * 8 + 4 * (t >> 1)) * 4;
    const uint32_t part0 = smem_u32(&tl->part[0][0]);

    uint4 qf[4];
    {
        const __nv_bfloat16* xb = x + b * kD;
        const uint4 r0 = __ldg(reinterpret_cast<const uint4*>(xb + lane * 8));
        const uint4 r1 = __ldg(reinterpret_cast<const uint4*>(xb + 256 + lane * 8));
        const float xe = __bfloat162float(__ldg(xb + rank * 256 + (lane >> 4) * 128 + warp * 16 + (lane & 15)));
        float mean, den;
        ln_stats(r0, r1, mean, den);
        tl->ps[warp][lane] = bf_bits(ln_apply(xe, mean, den));
        STAMP(tid == 0, 10);
        asm volatile("barrier.cluster.wait.aligned;" ::: "memory");
#pragma unroll
        for (int i = 0; i < 16; i++) (&acc[0][0][0])[i] = 0.f;
#pragma unroll 1
        for (int i = 0; i < 2; i++) wsum_tile(i);
        STAMP(tid == 0, 11);
        float o4[4];
        quad_reduce(o4);
        const uint32_t dst = part0 + (rank * 8 + warp) * 512 + (t & 1) * 256 + pcol;
        const uint32_t xq = smem_u32(&tl->xq);
        st_async4(mapa(dst, rank ^ 1), o4[0], o4[1], o4[2], o4[3], mapa(xq, rank ^ 1));
        st_async4(mapa(dst, rank), o4[0], o4[1], o4[2], o4[3], mapa(xq, rank));
        if (tid < 128) {
            mbar_wait(xq, 0);
            STAMP(tid == 0, 13);
            float sum = 0.f;
#pragma unroll
            for (int i = 0; i < 16; i++) sum += tl->part[i][tid];
            reinterpret_cast<unsigned short*>(tl->vec[0])[tid] = (unsigned short)bf_bits(sum);
        }
        asm volatile("bar.sync 1, 256;" ::: "memory");
#pragma unroll
        for (int j = 0; j < 4; j++) qf[j] = lds128(smem_u32(tl->vec[0]) + (4 * (j ^ (g & 1)) + t) * 16);
    }
    STAMP(tid == 0, 1);

    {
        const uint32_t a0 = ring + (warp * 16 + g) * 256 + t * 16;
#pragma unroll 1
        for (int i = 0; i < kNT; i++) {
            mbar_wait(full0 + 8 * s, ph);
            uint4 ka[4], kb[4];
#pragma unroll
            for (int j = 0; j < 4; j++) {
                const uint32_t a = a0 + s * kSlotBytes + (j ^ (g & 1)) * 64;
                ka[j] = lds128(a);
                kb[j] = lds128(a + 8 * 256);
            }
            __syncwarp();
            if (lane == 0) mbar_arrive(empty0 + 8 * s);
            float c0[4] = {}, c1[4] = {};
#pragma unroll
            for (int j = 0; j < 4; j++) {
                mma16816(c0, ka[j].x, kb[j].x, ka[j].y, kb[j].y, qf[j].x, qf[j].y);
                mma16816(c1, ka[j].z, kb[j].z, ka[j].w, kb[j].w, qf[j].z, qf[j].w);
            }
            const float sa = (g & 1) ? c0[1] + c1[1] : c0[0] + c1[0];
            const float sb = (g & 1) ? c0[3] + c1[3] : c0[2] + c1[2];
            const float sc = bf_round(bf_round((t & 1) ? sb : sa) * 0.08838834764831845f);
            if (t < 2) tl->ps[warp][i * 16 + t * 8 + g] = __float_as_uint(sc);
            if (++s == kSlots) { s = 0; ph ^= 1; }
        }
    }
    STAMP(tid == 0, 2);
    {
        __syncwarp();
        const uint32_t pa = smem_u32(&tl->ps[warp][lane * 4]);
        const uint4 s0 = lds128(pa), s1 = lds128(pa + 512);
        float sv[8] = {__uint_as_float(s0.x), __uint_as_float(s0.y), __uint_as_float(s0.z), __uint_as_float(s0.w),
                       __uint_as_float(s1.x), __uint_as_float(s1.y), __uint_as_float(s1.z), __uint_as_float(s1.w)};
        float m = sv[0];
#pragma unroll
        for (int i = 1; i < 8; i++) m = fmaxf(m, sv[i]);
        m = warp_max(m);
        float l = 0.f;
#pragma unroll
        for (int i = 0; i < 8; i++) l += __expf(sv[i] - m);
        l = warp_sum(l);
        const uint32_t xml = smem_u32(&tl->xml);
        if (lane < 2) st_async2(mapa(smem_u32(&tl->ml[rank * 8 + warp]), lane), m, l, mapa(xml, lane));
        STAMP(tid == 0, 14);
        mbar_wait(xml, 0);
        STAMP(tid == 0, 15);
        const float2 e = tl->ml[lane & 15];
        float gm = e.x;
#pragma unroll
        for (int o = 8; o; o >>= 1) gm = fmaxf(gm, __shfl_xor_sync(0xFFFFFFFFu, gm, o));
        float gl = e.y * __expf(e.x - gm);
#pragma unroll
        for (int o = 8; o; o >>= 1) gl += __shfl_xor_sync(0xFFFFFFFFu, gl, o);
        const float inv = __frcp_rn(gl);
        uint32_t pb[8];
#pragma unroll
        for (int i = 0; i < 8; i++) pb[i] = bf_bits(__expf(sv[i] - gm) * inv);
        *reinterpret_cast<uint4*>(&tl->ps[warp][lane * 4]) = make_uint4(pb[0], pb[1], pb[2], pb[3]);
        *reinterpret_cast<uint4*>(&tl->ps[warp][128 + lane * 4]) = make_uint4(pb[4], pb[5], pb[6], pb[7]);
        __syncwarp();
    }
    STAMP(tid == 0, 3);
    uint4 wf[2][8];
    auto wo_chunk = [&](uint4 (&w)[8]) {
        mbar_wait(full0 + 8 * s, ph);
#pragma unroll
        for (int u = 0; u < 8; u++) w[u] = lds128(ring + s * kSlotBytes + t * kWoPitch + u * 1024 + (warp * 8 + g) * 16);
        __syncwarp();
        if (lane == 0) mbar_arrive(empty0 + 8 * s);
        if (++s == kSlots) { s = 0; ph ^= 1; }
    };
#pragma unroll
    for (int i = 0; i < 16; i++) (&acc[0][0][0])[i] = 0.f;
#pragma unroll 1
    for (int i = 0; i < kNT; i++) {
        if (i == WOA) wo_chunk(wf[0]);
        if (i == WOB) wo_chunk(wf[1]);
        wsum_tile(i);
    }
    STAMP(tid == 0, 4);
    {
        float o4[4];
        quad_reduce(o4);
        const uint32_t xo = smem_u32(&tl->xo);
        st_async4(mapa(part0 + (rank * 8 + warp) * 256 + pcol, t & 1), o4[0], o4[1], o4[2], o4[3], mapa(xo, t & 1));
        if (tid < 64) {
            mbar_wait(xo, 0);
            STAMP(tid == 0, 12);
            const float* pp = &tl->part[0][0] + tid;
            float s4[4];
#pragma unroll
            for (int i = 0; i < 4; i++) s4[i] = (pp[i * 256] + pp[i * 256 + 64]) + (pp[i * 256 + 128] + pp[i * 256 + 192]);
            const uint32_t ob = bf_bits((s4[0] + s4[1]) + (s4[2] + s4[3]));
            tl->vec[0][tid] = ob;
            tl->vec[1][tid] = ob << 16;
        }
        if (WOA == kNT) wo_chunk(wf[0]);
        if (WOB == kNT) wo_chunk(wf[1]);
        asm volatile("bar.sync 2, 288;" ::: "memory");
    }
    STAMP(tid == 0, 6);
    {
        float y[2][2][4] = {};
        const uint32_t va = smem_u32(&tl->vec[g & 1][t * 8]);
#pragma unroll
        for (int k = 0; k < 2; k++)
#pragma unroll
            for (int c = 0; c < 2; c++) {
                const uint4 ow = lds128(va + c * 128 + k * 16);
                const uint4(&w)[8] = wf[c];
                mma16816(y[c][0], w[4 * k].x, w[4 * k].y, w[4 * k + 1].x, w[4 * k + 1].y, ow.x, ow.y);
                mma16816(y[c][1], w[4 * k].z, w[4 * k].w, w[4 * k + 1].z, w[4 * k + 1].w, ow.x, ow.y);
                mma16816(y[c][0], w[4 * k + 2].x, w[4 * k + 2].y, w[4 * k + 3].x, w[4 * k + 3].y, ow.z, ow.w);
                mma16816(y[c][1], w[4 * k + 2].z, w[4 * k + 2].w, w[4 * k + 3].z, w[4 * k + 3].w, ow.z, ow.w);
            }
        uint32_t bits[2];
#pragma unroll
        for (int e = 0; e < 2; e++) {
            const float lo = (t & 1) ? y[0][0][2 + e] + y[1][0][2 + e] : y[0][0][e] + y[1][0][e];
            const float hi = (t & 1) ? y[0][1][2 + e] + y[1][1][2 + e] : y[0][1][e] + y[1][1][e];
            bits[e] = __float_as_uint((t & 2) ? hi : lo);
            if (bits[e] == kEmpty) bits[e] = 0x7FFFFFFFu;
        }
        uint32_t* dst = &g_slots[b][warp * 8 + g][2 * h + rank][2 * t];
        asm volatile("st.relaxed.gpu.global.v2.u32 [%0], {%1, %2};" ::"l"(dst), "r"(bits[0]), "r"(bits[1]) : "memory");
    }
    STAMP(tid == 0, 7);
}

typedef CUresult (*EncodeTiled)(CUtensorMap*, CUtensorMapDataType, cuuint32_t, void*, const cuuint64_t*, const cuuint64_t*,
                                const cuuint32_t*, const cuuint32_t*, CUtensorMapInterleave, CUtensorMapSwizzle,
                                CUtensorMapL2promotion, CUtensorMapFloatOOBfill);

}

extern "C" void kernel_launch(void* const* d_in, const int* in_sizes, int n_in, void* d_out, int out_size) {
    (void)in_sizes; (void)n_in; (void)out_size;
    static EncodeTiled encode = nullptr;
    if (!encode) {
        cudaFuncSetAttribute(fused_decode_kernel, cudaFuncAttributeMaxDynamicSharedMemorySize, kSmemBytes);
        void* fn = nullptr;
        cudaDriverEntryPointQueryResult st;
        cudaGetDriverEntryPoint("cuTensorMapEncodeTiled", &fn, cudaEnableDefault, &st);
        encode = (EncodeTiled)fn;
    }
    CUtensorMap wqmap, w1map;
    const cuuint32_t ones[2] = {1, 1};
    {
        const cuuint64_t dim[2] = {kH * kDh, kD}, stride[1] = {kH * kDh * 2};
        const cuuint32_t box[2] = {kDh, 128};
        encode(&wqmap, CU_TENSOR_MAP_DATA_TYPE_BFLOAT16, 2, d_in[3], dim, stride, box, ones, CU_TENSOR_MAP_INTERLEAVE_NONE,
               CU_TENSOR_MAP_SWIZZLE_NONE, CU_TENSOR_MAP_L2_PROMOTION_L2_256B, CU_TENSOR_MAP_FLOAT_OOB_FILL_NONE);
    }
    {
        const cuuint64_t dim[2] = {kF / 2, kD}, stride[1] = {kF * 2};
        const cuuint32_t box[2] = {kFc / 2, 32};
        encode(&w1map, CU_TENSOR_MAP_DATA_TYPE_UINT32, 2, d_in[6], dim, stride, box, ones, CU_TENSOR_MAP_INTERLEAVE_NONE,
               CU_TENSOR_MAP_SWIZZLE_NONE, CU_TENSOR_MAP_L2_PROMOTION_L2_256B, CU_TENSOR_MAP_FLOAT_OOB_FILL_NONE);
    }
    typedef const __nv_bfloat16* P;
    fused_decode_kernel<<<kCtas, kThreads, kSmemBytes, cudaStreamPerThread>>>(
        wqmap, w1map, (P)d_in[0], (P)d_in[1], (P)d_in[2], (P)d_in[4], (P)d_in[7], (P)d_in[8], (P)d_in[9],
        (__nv_bfloat16*)d_out);
}
```

```cpp
#include <cuda.h>
#include <cuda_runtime.h>
#include <cuda_bf16.h>
#include <stdint.h>

namespace {

constexpr int kD = 512, kH = 32, kDh = 128, kSk = 16384, kWin = 4096, kF = 1376;
constexpr int kAttCtas = 128, kFfnCtas = 4, kCtas = kAttCtas + kFfnCtas;
constexpr int kThreads = 288;
constexpr int kKeysPerCta = kWin / 2;
constexpr int kTileBytes = 128 * 256;
constexpr int kNT = kKeysPerCta / 128;
#define SLOTS 6
#define LIM 4
#define LIM0 4
#define LIME 3
#define NEND 6
#define WOA 4
#define WOB 8
#define KFIRST 2
#define FLIM1 5
#define FLIM2 4
constexpr int kSlots = SLOTS;
#define LASTSUB 4
#define NSPLIT 3
#define TAU 1300
#define LEAD 3000
#define PWARP 0
#define PAIRMAP 1
#define PREF 2
#define PSKIP 32
#define PSTR 64
#define ACCW 4
#define ACCPAD 2
constexpr int kSlotBytes = kTileBytes;
constexpr int kChunks = 2 + 2 * kNT + 2;
constexpr int kPiece = kTileBytes / LASTSUB;
static_assert(LASTSUB == 4, "pieces belong to warp pairs");
constexpr int kRingBytes = kSlots * kSlotBytes;
constexpr uint32_t kWaitCycles = 1u << 30;

constexpr int kFc = 352;
constexpr int kFch = kFc / 8;

struct __align__(16) Tail {
    float part[8][128];
    float peer[128];
    uint32_t ps[8][256];
    unsigned short vec[128];
    float2 ml[16];
    unsigned long long full[kSlots], empty[kSlots], last[NSPLIT * LASTSUB], xq, xo, xml;
};
constexpr int kSmemBytes = kRingBytes + (int)sizeof(Tail);

struct Scratch {
    unsigned long long acc[2 * kD * ACCPAD * 4 / ACCW], ffn[2 * kD];
};
__device__ __align__(128) Scratch g_scratch;

#define STAMP(cond, i) do { } while (0)

__device__ __forceinline__ uint32_t smem_u32(const void* p) { return (uint32_t)__cvta_generic_to_shared(p); }
__device__ __forceinline__ void mbar_init(uint32_t a, uint32_t c) {
    asm volatile("mbarrier.init.shared::cta.b64 [%0], %1;" ::"r"(a), "r"(c) : "memory");
}
__device__ __forceinline__ void mbar_expect(uint32_t a, uint32_t bytes) {
    asm volatile("mbarrier.arrive.expect_tx.shared::cta.b64 _, [%0], %1;" ::"r"(a), "r"(bytes) : "memory");
}
__device__ __forceinline__ void mbar_arrive(uint32_t a) {
    asm volatile("mbarrier.arrive.shared::cta.b64 _, [%0];" ::"r"(a) : "memory");
}
__device__ __forceinline__ void check_timeout(uint32_t t0) {
    if ((uint32_t)clock() - t0 > kWaitCycles) __trap();
}
__device__ __forceinline__ uint32_t timer_ns() {
    uint32_t t;
    asm volatile("mov.u32 %0, %%globaltimer_lo;" : "=r"(t));
    return t;
}
__device__ __forceinline__ bool mbar_try(uint32_t a, uint32_t parity) {
    uint32_t ok;
    asm volatile("{\n.reg .pred p;\nmbarrier.try_wait.parity.shared::cta.b64 p, [%1], %2;\nselp.u32 %0, 1, 0, p;\n}"
                 : "=r"(ok) : "r"(a), "r"(parity) : "memory");
    return ok;
}
__device__ __forceinline__ void mbar_wait(uint32_t a, uint32_t parity) {
    if (mbar_try(a, parity)) return;
    const uint32_t t0 = clock();
    while (!mbar_try(a, parity)) check_timeout(t0);
}
__device__ __forceinline__ void bulk_load(uint32_t dst, const void* src, uint32_t bytes, uint32_t bar, uint64_t pol) {
    asm volatile("cp.async.bulk.shared::cluster.global.mbarrier::complete_tx::bytes.L2::cache_hint [%0], [%1], %2, [%3], %4;"
                 ::"r"(dst), "l"(src), "r"(bytes), "r"(bar), "l"(pol) : "memory");
}
__device__ __forceinline__ void tensor_load(uint32_t dst, const CUtensorMap* map, int c0, int c1, uint32_t bar) {
    asm volatile("cp.async.bulk.tensor.2d.shared::cluster.global.mbarrier::complete_tx::bytes [%0], [%1, {%2, %3}], [%4];"
                 ::"r"(dst), "l"(map), "r"(c0), "r"(c1), "r"(bar) : "memory");
}
__device__ __forceinline__ uint32_t mapa(uint32_t a, uint32_t rank) {
    uint32_t r;
    asm("mapa.shared::cluster.u32 %0, %1, %2;" : "=r"(r) : "r"(a), "r"(rank));
    return r;
}
__device__ __forceinline__ void st_async2(uint32_t dst, float a, float b, uint32_t bar) {
    asm volatile("st.async.shared::cluster.mbarrier::complete_tx::bytes.v2.f32 [%0], {%1, %2}, [%3];"
                 ::"r"(dst), "f"(a), "f"(b), "r"(bar) : "memory");
}
__device__ __forceinline__ uint4 lds128(uint32_t a) {
    uint4 v;
    asm volatile("ld.shared.v4.u32 {%0, %1, %2, %3}, [%4];" : "=r"(v.x), "=r"(v.y), "=r"(v.z), "=r"(v.w) : "r"(a) : "memory");
    return v;
}
__device__ __forceinline__ uint4 ldg128(const void* p) {
    uint4 v;
    asm volatile("ld.global.nc.v4.u32 {%0, %1, %2, %3}, [%4];" : "=r"(v.x), "=r"(v.y), "=r"(v.z), "=r"(v.w) : "l"(p));
    return v;
}
__device__ __forceinline__ float ldg_bf(const __nv_bfloat16* p) {
    unsigned short v;
    asm volatile("ld.global.nc.u16 %0, [%1];" : "=h"(v) : "l"(p));
    return __uint_as_float((uint32_t)v << 16);
}
__device__ __forceinline__ uint2 lds64(uint32_t a) {
    uint2 v;
    asm volatile("ld.shared.v2.u32 {%0, %1}, [%2];" : "=r"(v.x), "=r"(v.y) : "r"(a) : "memory");
    return v;
}
__device__ __forceinline__ uint4 ldsm_trans(uint32_t a) {
    uint4 v;
    asm volatile("ldmatrix.sync.aligned.m8n8.x4.trans.shared.b16 {%0, %1, %2, %3}, [%4];"
                 : "=r"(v.x), "=r"(v.y), "=r"(v.z), "=r"(v.w) : "r"(a) : "memory");
    return v;
}
__device__ __forceinline__ void word_add(unsigned long long* w, float v) {
    asm volatile("red.relaxed.gpu.global.add.f32 [%0], %1;" ::"l"(w), "f"(v) : "memory");
}
__device__ __forceinline__ uint2 word_count(unsigned long long* w, uint32_t hi) {
    unsigned long long r;
    asm volatile("atom.relaxed.gpu.global.add.u64 %0, [%1], %2;" : "=l"(r) : "l"(w), "l"((unsigned long long)hi << 32) : "memory");
    return make_uint2((uint32_t)r, (uint32_t)(r >> 32));
}
__device__ __forceinline__ void word_clear(unsigned long long* w) {
    asm volatile("st.relaxed.gpu.global.u64 [%0], %1;" ::"l"(w), "l"(0ULL) : "memory");
}
__device__ __forceinline__ int acc_index(int i) { return (i / ACCW) * (4 * ACCPAD) + (i % ACCW); }
__device__ __forceinline__ void mma16816(float (&c)[4], uint32_t a0, uint32_t a1, uint32_t a2, uint32_t a3,
                                         uint32_t b0, uint32_t b1) {
    asm volatile("mma.sync.aligned.m16n8k16.row.col.f32.bf16.bf16.f32 {%0, %1, %2, %3}, {%4, %5, %6, %7}, {%8, %9}, {%0, %1, %2, %3};"
                 : "+f"(c[0]), "+f"(c[1]), "+f"(c[2]), "+f"(c[3])
                 : "r"(a0), "r"(a1), "r"(a2), "r"(a3), "r"(b0), "r"(b1));
}
__device__ __forceinline__ uint32_t bf_pack(float hi, float lo) {
    uint32_t r;
    asm("cvt.rn.bf16x2.f32 %0, %1, %2;" : "=r"(r) : "f"(hi), "f"(lo));
    return r;
}
__device__ __forceinline__ uint32_t bf_bits(float f) { return bf_pack(0.f, f); }
__device__ __forceinline__ float bf_round(float f) { return __uint_as_float(bf_pack(f, 0.f)); }
__device__ __forceinline__ float bf_lo(uint32_t w) { return __uint_as_float(w << 16); }
__device__ __forceinline__ float bf_hi(uint32_t w) { return __uint_as_float(w & 0xFFFF0000u); }
__device__ __forceinline__ float warp_sum(float v) {
#pragma unroll
    for (int o = 16; o; o >>= 1) v += __shfl_xor_sync(0xFFFFFFFFu, v, o);
    return v;
}
__device__ __forceinline__ float warp_max(float v) {
#pragma unroll
    for (int o = 16; o; o >>= 1) v = fmaxf(v, __shfl_xor_sync(0xFFFFFFFFu, v, o));
    return v;
}

__device__ __forceinline__ void finish(__nv_bfloat16* dst, unsigned long long* w, float xv, uint32_t sum, uint32_t ffn_hi) {
    const uint32_t r = bf_bits(bf_round(xv + bf_round(__uint_as_float(sum))) + bf_hi(ffn_hi));
    asm volatile("st.global.u16 [%0], %1;" ::"l"(dst), "h"((unsigned short)r) : "memory");
    word_clear(w);
}

__device__ __forceinline__ void ln_stats(const uint4& r0, const uint4& r1, float& mean_bf, float& den_bf) {
    const uint32_t w[8] = {r0.x, r0.y, r0.z, r0.w, r1.x, r1.y, r1.z, r1.w};
    float s = 0.f;
#pragma unroll
    for (int i = 0; i < 8; i++) s += bf_lo(w[i]) + bf_hi(w[i]);
    const float mean = warp_sum(s) * (1.f / kD);
    float v = 0.f;
#pragma unroll
    for (int i = 0; i < 8; i++) {
        const float a = bf_lo(w[i]) - mean, c = bf_hi(w[i]) - mean;
        v += a * a + c * c;
    }
    const float var = warp_sum(v) * (1.f / kD);
    mean_bf = bf_round(mean);
    den_bf = bf_round(sqrtf(bf_round(bf_round(var) + 1e-5f)));
}
__device__ __forceinline__ float ln_apply(float x, float mean_bf, float den_bf) {
    return bf_round(bf_round(x - mean_bf) / den_bf);
}

__device__ __forceinline__ void fma8x2(float (&a)[2][8], const uint4& w, float2 s) {
    const uint32_t u[4] = {w.x, w.y, w.z, w.w};
#pragma unroll
    for (int i = 0; i < 4; i++) {
        const float lo = bf_lo(u[i]), hi = bf_hi(u[i]);
        a[0][2 * i] = fmaf(s.x, lo, a[0][2 * i]);
        a[0][2 * i + 1] = fmaf(s.x, hi, a[0][2 * i + 1]);
        a[1][2 * i] = fmaf(s.y, lo, a[1][2 * i]);
        a[1][2 * i + 1] = fmaf(s.y, hi, a[1][2 * i + 1]);
    }
}

__device__ __forceinline__ uint32_t kv_offset(uint32_t cta) {
    const uint32_t pair = cta >> 1;
    const uint32_t c8 = pair - 4, r7 = (pair * 37 - 36 * 37) >> 8;
    const uint32_t bh0 = ((pair & 1) << 5) + 30 + (pair >> 1);
    const uint32_t bh8 = ((c8 & 8) << 2) + (c8 & 7) + ((c8 >> 1) & 8);
    const uint32_t bh7 = ((r7 & 1) << 5) + pair - 20 - ((r7 + 1) >> 1) * 7;
    const uint32_t bh = pair < 4 ? bh0 : pair < 36 ? bh8 : bh7;
    return (bh * kSk + (kSk - kWin) + (cta & 1) * kKeysPerCta) * (kDh * 2);
}

constexpr int kFStages = kSlots - 1, kF1 = kD / 32;
__device__ __forceinline__ void ffn_cta(unsigned char* smem, int f, const __nv_bfloat16* x, const CUtensorMap* w1map,
                                        const __nv_bfloat16* b1, const __nv_bfloat16* w2,
                                        const __nv_bfloat16* b2, __nv_bfloat16* out, Scratch* sc) {
    const uint32_t ring = smem_u32(smem);
    const uint32_t full0 = ring + kRingBytes, empty0 = full0 + 64;
    float2* xs = reinterpret_cast<float2*>(smem + kFStages * kSlotBytes);
    float2* hs = xs + kD;
    float* red = reinterpret_cast<float*>(hs + kFc);
    const int tid = threadIdx.x, warp = tid >> 5, lane = tid & 31;
    const int cols = min(kFc, kF - f * kFc), n2 = cols / 32;
    if (warp > 8) return;
    if (warp == 8) {
        if (lane == 0) {
            for (int s = 0; s < kFStages; s++) { mbar_init(full0 + 8 * s, 1); mbar_init(empty0 + 8 * s, 8); }
            asm volatile("fence.mbarrier_init.release.cluster;" ::: "memory");
        }
        __syncwarp();
        asm volatile("bar.arrive 1, 288;" ::: "memory");
        if (lane == 0) {
            uint64_t pol;
            asm volatile("createpolicy.fractional.L2::evict_first.b64 %0, 1.0;" : "=l"(pol));
            int s = 0, ph = 1, landed = 0;
#pragma unroll 1
            for (int i = 0; i < kF1 + n2; i++) {
                for (; landed <= i - (i < kF1 ? FLIM1 : FLIM2); landed++)
                    mbar_wait(full0 + 8 * (landed % kFStages), (landed / kFStages) & 1);
                mbar_wait(empty0 + 8 * s, ph);
                if (i < kF1) {
                    mbar_expect(full0 + 8 * s, 32 * 768);
                    tensor_load(ring + s * kSlotBytes, w1map, (f * kFc / 2) & ~31, i * 16, full0 + 8 * s);
                    tensor_load(ring + s * kSlotBytes + 16 * 768, w1map, ((kF + f * kFc) / 2) & ~31, i * 16, full0 + 8 * s);
                } else {
                    mbar_expect(full0 + 8 * s, kTileBytes);
                    bulk_load(ring + s * kSlotBytes, w2 + (size_t)(f * kFc + (i - kF1) * 32) * kD, kTileBytes, full0 + 8 * s, pol);
                }
                if (++s == kFStages) { s = 0; ph ^= 1; }
            }
        }
        return;
    }
    float xo[4], bo[2];
    {
        const __nv_bfloat16* xb = x + (warp & 1) * kD;
        const uint4 r0 = ldg128(xb + lane * 8), r1 = ldg128(xb + 256 + lane * 8);
        const int i0 = (warp >> 1) * 32 + lane;
        float xe[4];
#pragma unroll
        for (int k = 0; k < 4; k++) xe[k] = ldg_bf(xb + i0 + k * 128);
        const float ba = ldg_bf(b1 + f * kFc + tid), bb = ldg_bf(b1 + f * kFc + min(tid + 256, cols - 1));
#pragma unroll
        for (int k = 0; k < 4; k++) xo[k] = ldg_bf(x + tid + k * 256);
        bo[0] = ldg_bf(b2 + tid); bo[1] = ldg_bf(b2 + tid + 256);
        float mean, den;
        ln_stats(r0, r1, mean, den);
#pragma unroll
        for (int k = 0; k < 4; k++) reinterpret_cast<float*>(xs)[2 * (i0 + k * 128) + (warp & 1)] = ln_apply(xe[k], mean, den);
        hs[tid] = make_float2(ba, ba);
        if (tid + 256 < kFc) hs[tid + 256] = make_float2(bb, bb);
    }
    asm volatile("bar.sync 1, 288;" ::: "memory");
    STAMP(tid == 0, 1);
    int s = 0, ph = 0, c = tid % kFch, rg = tid / kFch, width = kFc, stages = kF1, pitch = 768;
    uint32_t base0 = ring + rg * 4 * 768 + c * 16 + (f & 1) * 64, base1 = ring + (16 + rg * 4) * 768 + c * 16 + ((f & 1) ^ 1) * 64;
    const float2* act = xs;
#pragma unroll 1
    for (int phase = 0; phase < 2; phase++) {
        float a[2][8] = {};
#pragma unroll 1
        for (int i = 0; i < stages; i++) {
            mbar_wait(full0 + 8 * s, ph);
            if (rg < 4) {
#pragma unroll
                for (int j = 0; j < 4; j++) {
                    fma8x2(a, lds128(base0 + s * kSlotBytes + j * pitch), act[i * 32 + rg * 8 + 2 * j]);
                    fma8x2(a, lds128(base1 + s * kSlotBytes + j * pitch), act[i * 32 + rg * 8 + 2 * j + 1]);
                }
            }
            __syncwarp();
            if (lane == 0) mbar_arrive(empty0 + 8 * s);
            if (++s == kFStages) { s = 0; ph ^= 1; }
        }
        if (rg < 4) {
#pragma unroll
            for (int bb = 0; bb < 2; bb++)
#pragma unroll
                for (int i = 0; i < 8; i++) red[(rg * 2 + bb) * width + c * 8 + i] = a[bb][i];
        }
        asm volatile("bar.sync 2, 256;" ::: "memory");
        STAMP(tid == 0, 2 + phase);
        if (phase) break;
#pragma unroll 1
        for (int i = tid; i < 2 * kFc; i += 256) {
            const float sum = (red[i] + red[2 * kFc + i]) + (red[4 * kFc + i] + red[6 * kFc + i]);
            float* hp = reinterpret_cast<float*>(hs) + (i < kFc ? 2 * i : 2 * (i - kFc) + 1);
            const float h = bf_round(bf_round(sum) + *hp);
            const float inner = 0.7978845608028654f * (h + 0.044715f * h * h * h);
            *hp = bf_round(0.5f * h * (1.f + tanhf(inner)));
        }
        asm volatile("bar.sync 2, 256;" ::: "memory");
        c = tid & 63; rg = tid >> 6; width = kD; stages = n2; pitch = 2048; act = hs;
        base0 = ring + rg * 8192 + c * 16; base1 = base0 + 1024;
    }
    uint2 old[4];
#pragma unroll
    for (int k = 0; k < 4; k++) {
        const int i = tid + k * 256;
        word_add(&sc->ffn[i], (red[i] + red[2 * kD + i]) + (red[4 * kD + i] + red[6 * kD + i]));
        old[k] = word_count(&sc->ffn[i], 1);
    }
#pragma unroll
    for (int k = 0; k < 4; k++) {
        const int i = tid + k * 256;
        const bool last = old[k].y == kFfnCtas - 1;
        const uint32_t ffn = bf_pack(bf_round(__uint_as_float(old[k].x)) + bo[k & 1], 0.f);
        old[k].y = 0;
        if (last) {
            word_clear(&sc->ffn[i]);
            old[k] = word_count(&sc->acc[acc_index(i)], ffn | 1);
            old[k].y |= ffn;
        }
    }
#pragma unroll
    for (int k = 0; k < 4; k++) {
        const int i = tid + k * 256;
        if ((old[k].y & 0xFF) == kH) finish(out + i, &sc->acc[acc_index(i)], xo[k], old[k].x, old[k].y);
    }
    STAMP(tid == 0, 9);
}

__global__ void __cluster_dims__(2, 1, 1) __launch_bounds__(kThreads, 1)
fused_decode_kernel(const __nv_bfloat16* __restrict__ x, const __nv_bfloat16* __restrict__ kc,
                    const __nv_bfloat16* __restrict__ vc, Scratch* sc,
                    __nv_bfloat16* __restrict__ out, const __nv_bfloat16* __restrict__ b2,
                    const __nv_bfloat16* __restrict__ b1, const __nv_bfloat16* __restrict__ w2,
                    const __grid_constant__ CUtensorMap wqmap, const __grid_constant__ CUtensorMap womap,
                    const __grid_constant__ CUtensorMap w1map) {
    extern __shared__ __align__(1024) unsigned char smem[];
    Tail* tl = reinterpret_cast<Tail*>(smem + kRingBytes);
    const uint32_t ring = smem_u32(smem);
    const uint32_t full0 = smem_u32(tl->full), empty0 = smem_u32(tl->empty);
    if (PREF) {
        const uint32_t tx = threadIdx.x - PSKIP, c = blockIdx.x + (tx >> 10);
        const char* p = reinterpret_cast<const char*>(kc) + (kv_offset(c) + tx * PSTR);
#pragma unroll
        for (int i = 0; i < PREF; i++)
            asm volatile("{\n.reg .pred p;\nsetp.lt.u32 p, %1, 128;\n@p prefetch.global.L2 [%0];\n}" ::"l"(p + i * (kThreads - PSKIP) * PSTR), "r"(c) : "memory");
    }
    const uint32_t rank = blockIdx.x & 1, off = kv_offset(blockIdx.x);
    const int b = off >> 27, h = (off >> 22) & 31;
    const char* ksrc = reinterpret_cast<const char*>(kc) + off;
    uint64_t pol;
    asm volatile("createpolicy.fractional.L2::evict_first.b64 %0, 1.0;" : "=l"(pol));
    if (threadIdx.x == PWARP * 32 && blockIdx.x < kAttCtas) {
#pragma unroll
        for (int s = 2; s < 2 + KFIRST; s++) {
            mbar_init(full0 + 8 * s, 1);
            asm volatile("fence.mbarrier_init.release.cluster;" ::: "memory");
            mbar_expect(full0 + 8 * s, kTileBytes);
            bulk_load(ring + s * kSlotBytes, ksrc + (s - 2) * kTileBytes, kTileBytes, full0 + 8 * s, pol);
        }
    }
    int tid = PWARP ? threadIdx.x : threadIdx.x < 32 ? threadIdx.x + 256 : threadIdx.x < 288 ? threadIdx.x - 32 : threadIdx.x;
    asm volatile("" : "+r"(tid));
    const int warp = __shfl_sync(0xFFFFFFFFu, tid >> 5, 0), lane = tid & 31;
    STAMP(tid == 0, 0);
    if (blockIdx.x >= kAttCtas) {
        ffn_cta(smem, blockIdx.x - kAttCtas, x, &w1map, b1, w2, b2, out, sc);
        return;
    }

    if (warp == 8) {
        const char* vsrc = reinterpret_cast<const char*>(vc) + off;
        uint32_t due = 0;
        if (lane == 0) {
#pragma unroll
            for (int s = 0; s < kSlots; s++)
                if (s < 2 || s >= 2 + KFIRST) mbar_init(full0 + 8 * s, 1);
            asm volatile("fence.mbarrier_init.release.cluster;" ::: "memory");
#pragma unroll
            for (int s = 0; s < 2; s++) {
                mbar_expect(full0 + 8 * s, kTileBytes);
                tensor_load(ring + s * kSlotBytes, &wqmap, h * kDh, rank * 256 + s * 128, full0 + 8 * s);
            }
#pragma unroll
            for (int s = 2 + KFIRST; s < LIM0; s++) {
                mbar_expect(full0 + 8 * s, kTileBytes);
                bulk_load(ring + s * kSlotBytes, ksrc + (s - 2) * kTileBytes, kTileBytes, full0 + 8 * s, pol);
            }
            if (TAU) due = timer_ns() + (LIM0 - 1) * TAU - LEAD;
#pragma unroll
            for (int s = 0; s < kSlots; s++) mbar_init(empty0 + 8 * s, 8);
#pragma unroll
            for (int s = 0; s < NSPLIT * LASTSUB; s++) mbar_init(smem_u32(&tl->last[s]), 1);
            mbar_init(smem_u32(&tl->xq), 1);
            mbar_init(smem_u32(&tl->xml), 1);
            mbar_init(smem_u32(&tl->xo), 1);
            mbar_expect(smem_u32(&tl->xq), 128 * 4);
            mbar_expect(smem_u32(&tl->xml), 16 * 8);
            mbar_expect(smem_u32(&tl->xo), 128 * 4);
            asm volatile("fence.mbarrier_init.release.cluster;" ::: "memory");
        }
        __syncwarp();
        asm volatile("barrier.cluster.arrive.relaxed.aligned;" ::: "memory");
        asm volatile("barrier.cluster.wait.aligned;" ::: "memory");
        if (lane == 0) {
            int s = LIM0 % kSlots, ph = LIM0 == kSlots ? 0 : 1;
            int landed = 0;
            const char* src = ksrc + (LIM0 - 2) * kTileBytes;
#pragma unroll 1
            for (int n = LIM0; n < kChunks; n++) {
                const int lim = n < kSlots ? LIM0 : n >= kChunks - NEND ? LIME : LIM;
                while (landed <= n - lim) {
                    const int m = landed < KFIRST ? landed + 2 : landed < KFIRST + 2 ? landed - KFIRST : landed;
                    if (m >= kChunks - NSPLIT) {
                        for (int u = 0; u < LASTSUB; u++) mbar_wait(smem_u32(&tl->last[(m - kChunks + NSPLIT) * LASTSUB + u]), 0);
                    } else if (m + kSlots >= n) {
                        mbar_wait(full0 + 8 * (m % kSlots), (m / kSlots) & 1);
                    }
                    landed++;
                }
                mbar_wait(empty0 + 8 * s, ph);
                if (n == 2 + kNT) src = vsrc;
                const bool split = n >= kChunks - NSPLIT, is_wo = n == 2 + kNT + WOA || n == 3 + kNT + WOB;
                const uint32_t dst = ring + s * kSlotBytes;
                if (TAU) {
                    due += is_wo ? TAU / 2 : TAU;
                    while ((int)(timer_ns() - due) < 0) { }
                }
                if (!split) mbar_expect(full0 + 8 * s, kTileBytes);
                if (split || is_wo) {
#pragma unroll
                    for (int u = 0; u < LASTSUB; u++) {
                        const uint32_t bar = split ? smem_u32(&tl->last[(n - kChunks + NSPLIT) * LASTSUB + u]) : full0 + 8 * s;
                        if (split) mbar_expect(bar, kPiece);
                        if (is_wo) tensor_load(dst + u * kPiece, &womap, rank * 256 + u * 64, h * kDh + (n == 2 + kNT + WOA ? 0 : 64), bar);
                        else bulk_load(dst + u * kPiece, src + u * kPiece, kPiece, bar, pol);
                    }
                } else {
                    bulk_load(dst, src, kTileBytes, full0 + 8 * s, pol);
                }
                if (!is_wo) src += kTileBytes;
                if (++s == kSlots) { s = 0; ph ^= 1; }
            }
            STAMP(true, 5);
        }
        return;
    }

    asm volatile("barrier.cluster.arrive.relaxed.aligned;" ::: "memory");
    const int g = lane >> 2, t = lane & 3;
    const __nv_bfloat16* xb = x + b * kD;
    const uint4 xr0 = ldg128(xb + lane * 8), xr1 = ldg128(xb + 256 + lane * 8);
    const float xe = ldg_bf(xb + rank * 256 + (lane >> 4) * 128 + warp * 16 + (lane & 15));
    const int ocol = rank * 256 + warp * 32 + t * 8 + g;
    const float xo = ldg_bf(xb + ocol);

    int s = 0, ph = 0, n = 0;
    auto chunk_wait = [&]() {
        const bool fin = n >= kChunks - NSPLIT;
        mbar_wait(fin ? smem_u32(&tl->last[(n - kChunks + NSPLIT) * LASTSUB + (warp >> 1)]) : full0 + 8 * s, fin ? 0 : ph);
    };
    auto chunk_done = [&]() {
        if (lane == 0) mbar_arrive(empty0 + 8 * s);
        n++;
        if (++s == kSlots) { s = 0; ph ^= 1; }
    };
    float acc[4][4];
    uint32_t mult = (g >> 1) == t ? (1u << ((g & 1) * 16)) : 0u;
    uint32_t va[4];
#pragma unroll
    for (int j = 0; j < 4; j++) va[j] = ring + (warp * 16 + t * 4) * 256 + (g >> 2) * 128 + (t ^ j) * 32 + (g & 3) * 8;
    asm volatile("" : "+r"(mult), "+r"(va[0]), "+r"(va[1]), "+r"(va[2]), "+r"(va[3]));
    const uint32_t pa0 = smem_u32(&tl->ps[warp][t * 4]);
    uint4 pw = make_uint4(0, 0, 0, 0);
    auto wsum_tile = [&](int i) {
        uint32_t bw[4] = {pw.x * mult, pw.y * mult, pw.z * mult, pw.w * mult};
        asm volatile("" : "+r"(bw[0]), "+r"(bw[1]), "+r"(bw[2]), "+r"(bw[3]));
        chunk_wait();
        STAMP(i == kNT - 1 && tid == 224, 20);
        uint2 v[4][4];
#pragma unroll
        for (int r = 0; r < 4; r += 2)
#pragma unroll
            for (int j = 0; j < 4; j++) {
                v[r][j] = lds64(va[j] + s * kSlotBytes + r * 256);
                v[r + 1][j] = lds64(va[j] + s * kSlotBytes + r * 256 + 256);
            }
        pw = lds128(pa0 + ((i + 1) & (kNT - 1)) * 64);
#pragma unroll
        for (int r = 0; r < 4; r += 2)
#pragma unroll
            for (int j = 0; j < 4; j++) mma16816(acc[j], v[r][j].x, v[r][j].y, v[r + 1][j].x, v[r + 1][j].y, bw[r], bw[r + 1]);
        chunk_done();
    };
    auto quad_reduce = [&](float (&o4)[4]) {
#pragma unroll
        for (int i = 0; i < 4; i++)
            o4[i] = (acc[0][i] + __shfl_xor_sync(0xFFFFFFFFu, acc[1][i], 1)) +
                    (__shfl_xor_sync(0xFFFFFFFFu, acc[2][i], 2) + __shfl_xor_sync(0xFFFFFFFFu, acc[3][i], 3));
    };
    uint32_t pdst = smem_u32(&tl->part[warp][64 * (g >> 2) + 16 * t + 4 * (g & 3)]);
    uint32_t psrc = smem_u32(&tl->part[0][tid & 127]);
    uint32_t rdst = mapa(psrc + 4096, rank ^ 1), rbar = mapa(smem_u32(&tl->xq), rank ^ 1);
    uint32_t odst = smem_u32(tl->vec) + ((tid >> 5) & 3) * 64 + ((tid >> 1) & 3) * 16 + ((tid >> 3) & 3) * 4 + (tid & 1) * 2;
    asm volatile("" : "+r"(pdst), "+r"(psrc), "+r"(rdst), "+r"(rbar), "+r"(odst));
    auto cluster_reduce = [&](int which) {
        float o4[4];
        quad_reduce(o4);
        asm volatile("st.shared.v4.f32 [%0], {%1, %2, %3, %4};" ::"r"(pdst), "f"(o4[0]), "f"(o4[1]), "f"(o4[2]), "f"(o4[3]) : "memory");
        STAMP(which && tid == 224, 18);
        if (warp < 4) {
            asm volatile("bar.sync 2, 256;" ::: "memory");
            float v[8];
#pragma unroll
            for (int i = 0; i < 8; i++) asm volatile("ld.shared.f32 %0, [%1];" : "=f"(v[i]) : "r"(psrc + i * 512) : "memory");
            const float mine = ((v[0] + v[1]) + (v[2] + v[3])) + ((v[4] + v[5]) + (v[6] + v[7]));
            asm volatile("st.async.shared::cluster.mbarrier::complete_tx::bytes.f32 [%0], %1, [%2];"
                         ::"r"(rdst), "f"(mine), "r"(rbar + which * 8) : "memory");
            STAMP(which && tid == 0, 19);
            mbar_wait(smem_u32(&tl->xq) + which * 8, 0);
            STAMP(tid == 0, 13 - which);
            float other;
            asm volatile("ld.shared.f32 %0, [%1];" : "=f"(other) : "r"(psrc + 4096) : "memory");
            asm volatile("st.shared.u16 [%0], %1;" ::"r"(which ? odst : smem_u32(&tl->vec[tid])), "h"((unsigned short)bf_bits(mine + other)) : "memory");
        } else {
            asm volatile("bar.arrive 2, 256;" ::: "memory");
        }
        asm volatile("bar.sync 1, 256;" ::: "memory");
    };

    uint2 qb[4];
    {
        float mean, den;
        ln_stats(xr0, xr1, mean, den);
        tl->ps[warp][lane] = bf_bits(ln_apply(xe, mean, den));
        STAMP(tid == 0, 10);
        asm volatile("barrier.cluster.wait.aligned;" ::: "memory");
        __syncwarp();
        pw = lds128(pa0);
#pragma unroll
        for (int i = 0; i < 16; i++) (&acc[0][0])[i] = 0.f;
#pragma unroll 1
        for (int i = 0; i < 2; i++) wsum_tile(i);
        STAMP(tid == 0, 11);
        cluster_reduce(0);
#pragma unroll
        for (int j = 0; j < 4; j++) {
            const uint4 w = lds128(smem_u32(tl->vec) + (4 * (j ^ ((g >> 1) & 1)) + t) * 16);
            qb[j] = (g & 1) ? make_uint2(w.y, w.w) : make_uint2(w.x, w.z);
        }
    }
    STAMP(tid == 0, 1);

    {
        const uint32_t a0 = ring + (warp * 16 + g) * 256 + t * 16 + (g & 1) * 64;
#pragma unroll 1
        for (int i = 0; i < kNT; i++) {
            mbar_wait(full0 + 8 * s, ph);
            uint4 kv[2][4];
#pragma unroll
            for (int j = 0; j < 4; j++) {
                const uint32_t a = (a0 ^ (j * 64)) + s * kSlotBytes;
                kv[0][j] = lds128(a);
                kv[1][j] = lds128(a + 8 * 256);
            }
            float c[2][4] = {};
#pragma unroll
            for (int j = 0; j < 4; j++)
#pragma unroll
                for (int u = 0; u < 2; u++) mma16816(c[u], kv[u][j].x, kv[u][j].y, kv[u][j].z, kv[u][j].w, qb[j].x, qb[j].y);
            chunk_done();
            const float dot = (t & 2) ? c[1][0] + c[1][3] : c[0][0] + c[0][3];
            const float sc2 = bf_round(bf_round(dot) * 0.08838834764831845f);
            if ((t & 1) == (g & 1)) tl->ps[warp][i * 16 + (t >> 1) * 8 + g] = __float_as_uint(sc2);
        }
    }
    STAMP(tid == 0, 2);
    {
        __syncwarp();
        const uint32_t pa = smem_u32(&tl->ps[warp][lane * 4]);
        const uint4 s0 = lds128(pa), s1 = lds128(pa + 512);
        float sv[8] = {__uint_as_float(s0.x), __uint_as_float(s0.y), __uint_as_float(s0.z), __uint_as_float(s0.w),
                       __uint_as_float(s1.x), __uint_as_float(s1.y), __uint_as_float(s1.z), __uint_as_float(s1.w)};
        float m = sv[0];
#pragma unroll
        for (int i = 1; i < 8; i++) m = fmaxf(m, sv[i]);
        m = warp_max(m);
        float l = 0.f;
#pragma unroll
        for (int i = 0; i < 8; i++) l += __expf(sv[i] - m);
        l = warp_sum(l);
        const uint32_t xml = smem_u32(&tl->xml);
        if (lane < 2) st_async2(mapa(smem_u32(&tl->ml[rank * 8 + warp]), lane), m, l, mapa(xml, lane));
        STAMP(tid == 0, 14);
        mbar_wait(xml, 0);
        STAMP(tid == 0, 15);
        const float2 e = tl->ml[lane & 15];
        float gm = e.x;
#pragma unroll
        for (int o = 8; o; o >>= 1) gm = fmaxf(gm, __shfl_xor_sync(0xFFFFFFFFu, gm, o));
        float gl = e.y * __expf(e.x - gm);
#pragma unroll
        for (int o = 8; o; o >>= 1) gl += __shfl_xor_sync(0xFFFFFFFFu, gl, o);
        const float inv = __frcp_rn(gl);
        uint32_t pb[8];
#pragma unroll
        for (int i = 0; i < 8; i++) pb[i] = bf_bits(__expf(sv[i] - gm) * inv);
        *reinterpret_cast<uint4*>(&tl->ps[warp][lane * 4]) = make_uint4(pb[0], pb[1], pb[2], pb[3]);
        *reinterpret_cast<uint4*>(&tl->ps[warp][128 + lane * 4]) = make_uint4(pb[4], pb[5], pb[6], pb[7]);
        __syncwarp();
    }
    STAMP(tid == 0, 3);
    uint32_t oa = smem_u32(&tl->vec[t * 8]);
    unsigned long long* word = &sc->acc[acc_index(b * kD + ocol)];
    __nv_bfloat16* optr = out + b * kD + ocol;
    asm volatile("" : "+l"(word), "+l"(optr), "+r"(oa));
    uint4 wf[2][4][2];
    uint32_t wa[2];
#pragma unroll
    for (int j = 0; j < 2; j++)
        wa[j] = ring + (warp >> 1) * kPiece + ((lane >> 4) * 8 + (lane & 7)) * 128 +
                (((warp & 1) * 4 + 2 * j + ((lane >> 3) & 1)) ^ (lane & 7)) * 16;
    asm volatile("" : "+r"(wa[0]), "+r"(wa[1]));
    auto wo_chunk = [&](uint4 (&w)[4][2]) {
        chunk_wait();
#pragma unroll
        for (int k = 0; k < 4; k++)
#pragma unroll
            for (int j = 0; j < 2; j++) w[k][j] = ldsm_trans(wa[j] + s * kSlotBytes + k * 2048);
        chunk_done();
    };
    pw = lds128(pa0);
#pragma unroll
    for (int i = 0; i < 16; i++) (&acc[0][0])[i] = 0.f;
#pragma unroll 1
    for (int i = 0; i < WOA; i++) wsum_tile(i);
    if (WOA < kNT) wo_chunk(wf[0]);
#pragma unroll 1
    for (int i = WOA; i < WOB; i++) wsum_tile(i);
    if (WOB < kNT) wo_chunk(wf[1]);
#pragma unroll 1
    for (int i = WOB; i < kNT; i++) wsum_tile(i);
    STAMP(tid == 0, 4);
    STAMP(tid == 224, 17);
    cluster_reduce(1);
    STAMP(tid == 0, 6);
    {
        float y[2][2][4] = {};
        uint4 ob[4];
#pragma unroll
        for (int k = 0; k < 4; k++) ob[k] = lds128(oa + k * 64);
#pragma unroll
        for (int c = 0; c < 2; c++) {
            if ((c ? WOB : WOA) == kNT) wo_chunk(wf[c]);
#pragma unroll
            for (int k = 0; k < 2; k++)
#pragma unroll
                for (int j = 0; j < 2; j++) {
                    const uint4 &w0 = wf[c][2 * k][j], &w1 = wf[c][2 * k + 1][j], &o = ob[2 * c + k];
                    mma16816(y[j][0], w0.x, w0.y, w0.z, w0.w, o.x, o.y);
                    mma16816(y[j][1], w1.x, w1.y, w1.z, w1.w, o.z, o.w);
                }
        }
        const float ya = (t & 1) ? y[0][0][2] + y[0][1][2] : y[0][0][0] + y[0][1][0];
        const float yb = (t & 1) ? y[1][0][2] + y[1][1][2] : y[1][0][0] + y[1][1][0];
        word_add(word, (t & 2) ? yb : ya);
        const uint2 r = word_count(word, 1);
        STAMP(tid == 0, 7);
        if ((r.y & 0xFF) == kH) finish(optr, word, xo, r.x, r.y);
        STAMP(tid == 0 && r.y != 0xFFFFFFFFu, 16);
    }
    STAMP(tid == 0, 9);
}

typedef CUresult (*EncodeTiled)(CUtensorMap*, CUtensorMapDataType, cuuint32_t, void*, const cuuint64_t*, const cuuint64_t*,
                                const cuuint32_t*, const cuuint32_t*, CUtensorMapInterleave, CUtensorMapSwizzle,
                                CUtensorMapL2promotion, CUtensorMapFloatOOBfill);

}

extern "C" void kernel_launch(void* const* d_in, const int* in_sizes, int n_in, void* d_out, int out_size) {
    (void)in_sizes; (void)n_in; (void)out_size;
    static EncodeTiled encode = nullptr;
    static Scratch* scratch = nullptr;
    if (!encode) {
        cudaGetSymbolAddress((void**)&scratch, g_scratch);
        cudaFuncSetAttribute(fused_decode_kernel, cudaFuncAttributeMaxDynamicSharedMemorySize, kSmemBytes);
        void* fn = nullptr;
        cudaDriverEntryPointQueryResult st;
        cudaGetDriverEntryPoint("cuTensorMapEncodeTiled", &fn, cudaEnableDefault, &st);
        encode = (EncodeTiled)fn;
    }
    CUtensorMap wqmap, womap, w1map;
    const cuuint32_t ones[2] = {1, 1};
    {
        const cuuint64_t dim[2] = {kH * kDh, kD}, stride[1] = {kH * kDh * 2};
        const cuuint32_t box[2] = {kDh, 128};
        encode(&wqmap, CU_TENSOR_MAP_DATA_TYPE_BFLOAT16, 2, d_in[3], dim, stride, box, ones, CU_TENSOR_MAP_INTERLEAVE_NONE,
               CU_TENSOR_MAP_SWIZZLE_NONE, CU_TENSOR_MAP_L2_PROMOTION_L2_256B, CU_TENSOR_MAP_FLOAT_OOB_FILL_NONE);
    }
    {
        const cuuint64_t dim[2] = {kD, kH * kDh}, stride[1] = {kD * 2};
        const cuuint32_t box[2] = {64, 64};
        encode(&womap, CU_TENSOR_MAP_DATA_TYPE_BFLOAT16, 2, d_in[4], dim, stride, box, ones, CU_TENSOR_MAP_INTERLEAVE_NONE,
               CU_TENSOR_MAP_SWIZZLE_128B, CU_TENSOR_MAP_L2_PROMOTION_L2_256B, CU_TENSOR_MAP_FLOAT_OOB_FILL_NONE);
    }
    {
        const cuuint64_t dim[2] = {kF, kD / 2}, stride[1] = {kF * 4};
        const cuuint32_t box[2] = {192, 16};
        encode(&w1map, CU_TENSOR_MAP_DATA_TYPE_UINT32, 2, d_in[6], dim, stride, box, ones, CU_TENSOR_MAP_INTERLEAVE_NONE,
               CU_TENSOR_MAP_SWIZZLE_NONE, CU_TENSOR_MAP_L2_PROMOTION_L2_256B, CU_TENSOR_MAP_FLOAT_OOB_FILL_NONE);
    }
    typedef const __nv_bfloat16* P;
    fused_decode_kernel<<<kCtas, kThreads, kSmemBytes, cudaStreamPerThread>>>(
        (P)d_in[0], (P)d_in[1], (P)d_in[2], scratch, (__nv_bfloat16*)d_out, (P)d_in[9], (P)d_in[7], (P)d_in[8],
        wqmap, womap, w1map);
}
```

```cpp
#include <cuda.h>
#include <cuda_runtime.h>
#include <cuda_bf16.h>
#include <stdint.h>

namespace {

constexpr int kD = 512, kH = 32, kDh = 128, kSk = 16384, kWin = 4096, kF = 1376;
constexpr int kAttCtas = 128, kFfnCtas = 4, kCtas = kAttCtas + kFfnCtas;
constexpr int kThreads = 320;
constexpr int kKeysPerCta = kWin / 2;
constexpr int kTileBytes = 128 * 256;
constexpr int kNT = kKeysPerCta / 128;
constexpr int kSlots = 6;
constexpr int kChunks = 2 + 2 * kNT + 2;
constexpr int kInFlight = 4;
constexpr int kSplit = 4;
constexpr int kPiece = kTileBytes / 4;
constexpr int kRingBytes = kSlots * kTileBytes;
constexpr int kWoSlot = (kChunks - 2) % kSlots;
static_assert(kWoSlot + 1 < kSlots, "the two wo chunks use neighbouring slots");
constexpr int kPeriod = 1320, kLead = 2800;
constexpr int kWoTime = 43100, kWoStagger = 1000, kWoGap = 96;
constexpr uint32_t kWaitCycles = 1u << 30;

constexpr int kFc = 352;
constexpr int kFch = kFc / 8;

struct __align__(16) Tail {
    float part[8][128];
    float peer[128];
    uint32_t ps[8][256];
    unsigned short vec[128];
    float2 ml[16];
    unsigned long long full[kSlots], empty[kSlots], last[kSplit * 4], xq, xo, vq, vo, xml;
};
constexpr int kSmemBytes = kRingBytes + (int)sizeof(Tail);

struct Scratch {
    unsigned long long acc[2 * kD * 4];
    unsigned long long ffn[2 * kD];
};
__device__ __align__(128) Scratch g_scratch;

__device__ __forceinline__ uint32_t smem_u32(const void* p) { return (uint32_t)__cvta_generic_to_shared(p); }
__device__ __forceinline__ void mbar_init(uint32_t a, uint32_t c) {
    asm volatile("mbarrier.init.shared::cta.b64 [%0], %1;" ::"r"(a), "r"(c) : "memory");
}
__device__ __forceinline__ void mbar_expect(uint32_t a, uint32_t bytes) {
    asm volatile("mbarrier.arrive.expect_tx.shared::cta.b64 _, [%0], %1;" ::"r"(a), "r"(bytes) : "memory");
}
__device__ __forceinline__ void mbar_arrive(uint32_t a) {
    asm volatile("mbarrier.arrive.shared::cta.b64 _, [%0];" ::"r"(a) : "memory");
}
__device__ __forceinline__ void check_timeout(uint32_t t0) {
    if ((uint32_t)clock() - t0 > kWaitCycles) __trap();
}
__device__ __forceinline__ uint32_t timer_ns() {
    uint32_t t;
    asm volatile("mov.u32 %0, %%globaltimer_lo;" : "=r"(t));
    return t;
}
__device__ __forceinline__ void wait_until(uint32_t due) {
    for (int it = 0; it < (1 << 16) && (int)(timer_ns() - due) < 0; it++) { }
}
__device__ __forceinline__ bool mbar_try(uint32_t a, uint32_t parity) {
    uint32_t ok;
    asm volatile("{\n.reg .pred p;\nmbarrier.try_wait.parity.shared::cta.b64 p, [%1], %2;\nselp.u32 %0, 1, 0, p;\n}"
                 : "=r"(ok) : "r"(a), "r"(parity) : "memory");
    return ok;
}
__device__ __forceinline__ bool mbar_test(uint32_t a, uint32_t parity) {
    uint32_t ok;
    asm volatile("{\n.reg .pred p;\nmbarrier.test_wait.parity.shared::cta.b64 p, [%1], %2;\nselp.u32 %0, 1, 0, p;\n}"
                 : "=r"(ok) : "r"(a), "r"(parity) : "memory");
    return ok;
}
__device__ __forceinline__ void mbar_wait(uint32_t a, uint32_t parity) {
    if (mbar_try(a, parity)) return;
    const uint32_t t0 = clock();
    while (!mbar_try(a, parity)) check_timeout(t0);
}
__device__ __forceinline__ void bulk_load(uint32_t dst, const void* src, uint32_t bytes, uint32_t bar, uint64_t pol) {
    asm volatile("cp.async.bulk.shared::cluster.global.mbarrier::complete_tx::bytes.L2::cache_hint [%0], [%1], %2, [%3], %4;"
                 ::"r"(dst), "l"(src), "r"(bytes), "r"(bar), "l"(pol) : "memory");
}
__device__ __forceinline__ void tensor_load(uint32_t dst, const CUtensorMap* map, int c0, int c1, uint32_t bar) {
    asm volatile("cp.async.bulk.tensor.2d.shared::cluster.global.mbarrier::complete_tx::bytes [%0], [%1, {%2, %3}], [%4];"
                 ::"r"(dst), "l"(map), "r"(c0), "r"(c1), "r"(bar) : "memory");
}
__device__ __forceinline__ uint32_t mapa(uint32_t a, uint32_t rank) {
    uint32_t r;
    asm("mapa.shared::cluster.u32 %0, %1, %2;" : "=r"(r) : "r"(a), "r"(rank));
    return r;
}
__device__ __forceinline__ void st_async2(uint32_t dst, float a, float b, uint32_t bar) {
    asm volatile("st.async.shared::cluster.mbarrier::complete_tx::bytes.v2.f32 [%0], {%1, %2}, [%3];"
                 ::"r"(dst), "f"(a), "f"(b), "r"(bar) : "memory");
}
__device__ __forceinline__ uint4 lds128(uint32_t a) {
    uint4 v;
    asm volatile("ld.shared.v4.u32 {%0, %1, %2, %3}, [%4];" : "=r"(v.x), "=r"(v.y), "=r"(v.z), "=r"(v.w) : "r"(a) : "memory");
    return v;
}
__device__ __forceinline__ uint4 ldg128(const void* p) {
    uint4 v;
    asm volatile("ld.global.nc.v4.u32 {%0, %1, %2, %3}, [%4];" : "=r"(v.x), "=r"(v.y), "=r"(v.z), "=r"(v.w) : "l"(p));
    return v;
}
__device__ __forceinline__ float ldg_bf(const __nv_bfloat16* p) {
    unsigned short v;
    asm volatile("ld.global.nc.u16 %0, [%1];" : "=h"(v) : "l"(p));
    return __uint_as_float((uint32_t)v << 16);
}
__device__ __forceinline__ uint2 lds64(uint32_t a) {
    uint2 v;
    asm volatile("ld.shared.v2.u32 {%0, %1}, [%2];" : "=r"(v.x), "=r"(v.y) : "r"(a) : "memory");
    return v;
}
__device__ __forceinline__ uint4 ldsm_trans(uint32_t a) {
    uint4 v;
    asm volatile("ldmatrix.sync.aligned.m8n8.x4.trans.shared.b16 {%0, %1, %2, %3}, [%4];"
                 : "=r"(v.x), "=r"(v.y), "=r"(v.z), "=r"(v.w) : "r"(a) : "memory");
    return v;
}
__device__ __forceinline__ void word_add(unsigned long long* w, float v) {
    asm volatile("red.relaxed.gpu.global.add.f32 [%0], %1;" ::"l"(w), "f"(v) : "memory");
}
__device__ __forceinline__ uint2 word_count(unsigned long long* w, uint32_t hi) {
    unsigned long long r;
    asm volatile("atom.relaxed.gpu.global.add.u64 %0, [%1], %2;" : "=l"(r) : "l"(w), "l"((unsigned long long)hi << 32) : "memory");
    return make_uint2((uint32_t)r, (uint32_t)(r >> 32));
}
__device__ __forceinline__ void word_clear(unsigned long long* w) {
    asm volatile("st.relaxed.gpu.global.u64 [%0], %1;" ::"l"(w), "l"(0ULL) : "memory");
}
__device__ __forceinline__ int acc_index(int i) { return (i >> 2) * 16 + (i & 3); }
__device__ __forceinline__ void mma16816(float (&c)[4], uint32_t a0, uint32_t a1, uint32_t a2, uint32_t a3,
                                         uint32_t b0, uint32_t b1) {
    asm volatile("mma.sync.aligned.m16n8k16.row.col.f32.bf16.bf16.f32 {%0, %1, %2, %3}, {%4, %5, %6, %7}, {%8, %9}, {%0, %1, %2, %3};"
                 : "+f"(c[0]), "+f"(c[1]), "+f"(c[2]), "+f"(c[3])
                 : "r"(a0), "r"(a1), "r"(a2), "r"(a3), "r"(b0), "r"(b1));
}
__device__ __forceinline__ uint32_t bf_pack(float hi, float lo) {
    uint32_t r;
    asm("cvt.rn.bf16x2.f32 %0, %1, %2;" : "=r"(r) : "f"(hi), "f"(lo));
    return r;
}
__device__ __forceinline__ uint32_t bf_bits(float f) { return bf_pack(0.f, f); }
__device__ __forceinline__ float bf_round(float f) { return __uint_as_float(bf_pack(f, 0.f)); }
__device__ __forceinline__ float bf_lo(uint32_t w) { return __uint_as_float(w << 16); }
__device__ __forceinline__ float bf_hi(uint32_t w) { return __uint_as_float(w & 0xFFFF0000u); }
__device__ __forceinline__ float warp_sum(float v) {
#pragma unroll
    for (int o = 16; o; o >>= 1) v += __shfl_xor_sync(0xFFFFFFFFu, v, o);
    return v;
}
__device__ __forceinline__ float warp_max(float v) {
#pragma unroll
    for (int o = 16; o; o >>= 1) v = fmaxf(v, __shfl_xor_sync(0xFFFFFFFFu, v, o));
    return v;
}

__device__ __forceinline__ void finish(__nv_bfloat16* dst, unsigned long long* w, float xv, uint32_t sum, uint32_t ffn_hi) {
    const uint32_t r = bf_bits(bf_round(xv + bf_round(__uint_as_float(sum))) + bf_hi(ffn_hi));
    asm volatile("st.global.u16 [%0], %1;" ::"l"(dst), "h"((unsigned short)r) : "memory");
    word_clear(w);
}

__device__ __forceinline__ void ln_stats(const uint4& r0, const uint4& r1, float& mean_bf, float& den_bf) {
    const uint32_t w[8] = {r0.x, r0.y, r0.z, r0.w, r1.x, r1.y, r1.z, r1.w};
    float s = 0.f;
#pragma unroll
    for (int i = 0; i < 8; i++) s += bf_lo(w[i]) + bf_hi(w[i]);
    const float mean = warp_sum(s) * (1.f / kD);
    float v = 0.f;
#pragma unroll
    for (int i = 0; i < 8; i++) {
        const float a = bf_lo(w[i]) - mean, c = bf_hi(w[i]) - mean;
        v += a * a + c * c;
    }
    const float var = warp_sum(v) * (1.f / kD);
    mean_bf = bf_round(mean);
    den_bf = bf_round(sqrtf(bf_round(bf_round(var) + 1e-5f)));
}
__device__ __forceinline__ float ln_apply(float x, float mean_bf, float den_bf) {
    return bf_round(bf_round(x - mean_bf) / den_bf);
}

__device__ __forceinline__ void fma8x2(float (&a)[2][8], const uint4& w, float2 s) {
    const uint32_t u[4] = {w.x, w.y, w.z, w.w};
#pragma unroll
    for (int i = 0; i < 4; i++) {
        const float lo = bf_lo(u[i]), hi = bf_hi(u[i]);
        a[0][2 * i] = fmaf(s.x, lo, a[0][2 * i]);
        a[0][2 * i + 1] = fmaf(s.x, hi, a[0][2 * i + 1]);
        a[1][2 * i] = fmaf(s.y, lo, a[1][2 * i]);
        a[1][2 * i + 1] = fmaf(s.y, hi, a[1][2 * i + 1]);
    }
}

__device__ __forceinline__ uint32_t kv_offset(uint32_t cta) {
    const uint32_t pair = cta >> 1;
    const uint32_t c8 = pair - 4, r7 = (pair * 37 - 36 * 37) >> 8;
    const uint32_t bh0 = ((pair & 1) << 5) + 30 + (pair >> 1);
    const uint32_t bh8 = ((c8 & 8) << 2) + (c8 & 7) + ((c8 >> 1) & 8);
    const uint32_t bh7 = ((r7 & 1) << 5) + pair - 20 - ((r7 + 1) >> 1) * 7;
    const uint32_t bh = pair < 4 ? bh0 : pair < 36 ? bh8 : bh7;
    return (bh * kSk + (kSk - kWin) + (cta & 1) * kKeysPerCta) * (kDh * 2);
}

constexpr int kFStages = kSlots - 1, kF1 = kD / 32;
__device__ __forceinline__ void ffn_cta(unsigned char* smem, int f, const __nv_bfloat16* x, const CUtensorMap* w1map,
                                        const __nv_bfloat16* b1, const __nv_bfloat16* w2,
                                        const __nv_bfloat16* b2, __nv_bfloat16* out, Scratch* sc) {
    const uint32_t ring = smem_u32(smem);
    const uint32_t full0 = ring + kRingBytes, empty0 = full0 + 64;
    float2* xs = reinterpret_cast<float2*>(smem + kFStages * kTileBytes);
    float2* hs = xs + kD;
    float* red = reinterpret_cast<float*>(hs + kFc);
    const int tid = threadIdx.x, warp = tid >> 5, lane = tid & 31;
    const int cols = min(kFc, kF - f * kFc), n2 = cols / 32;
    if (warp > 8) return;
    if (warp == 8) {
        if (lane == 0) {
            for (int s = 0; s < kFStages; s++) { mbar_init(full0 + 8 * s, 1); mbar_init(empty0 + 8 * s, 8); }
            asm volatile("fence.mbarrier_init.release.cluster;" ::: "memory");
        }
        __syncwarp();
        asm volatile("bar.arrive 1, 288;" ::: "memory");
        if (lane == 0) {
            uint64_t pol;
            asm volatile("createpolicy.fractional.L2::evict_first.b64 %0, 1.0;" : "=l"(pol));
            int s = 0, ph = 1, landed = 0;
#pragma unroll 1
            for (int i = 0; i < kF1 + n2; i++) {
                for (; landed <= i - (i < kF1 ? kFStages : kInFlight); landed++)
                    mbar_wait(full0 + 8 * (landed % kFStages), (landed / kFStages) & 1);
                mbar_wait(empty0 + 8 * s, ph);
                if (i < kF1) {
                    mbar_expect(full0 + 8 * s, 32 * 768);
                    tensor_load(ring + s * kTileBytes, w1map, (f * kFc / 2) & ~31, i * 16, full0 + 8 * s);
                    tensor_load(ring + s * kTileBytes + 16 * 768, w1map, ((kF + f * kFc) / 2) & ~31, i * 16, full0 + 8 * s);
                } else {
                    mbar_expect(full0 + 8 * s, kTileBytes);
                    bulk_load(ring + s * kTileBytes, w2 + (size_t)(f * kFc + (i - kF1) * 32) * kD, kTileBytes, full0 + 8 * s, pol);
                }
                if (++s == kFStages) { s = 0; ph ^= 1; }
            }
        }
        return;
    }
    float xo[4], bo[2];
    {
        const __nv_bfloat16* xb = x + (warp & 1) * kD;
        const uint4 r0 = ldg128(xb + lane * 8), r1 = ldg128(xb + 256 + lane * 8);
        const int i0 = (warp >> 1) * 32 + lane;
        float xe[4];
#pragma unroll
        for (int k = 0; k < 4; k++) xe[k] = ldg_bf(xb + i0 + k * 128);
        const float ba = ldg_bf(b1 + f * kFc + tid), bb = ldg_bf(b1 + f * kFc + min(tid + 256, cols - 1));
#pragma unroll
        for (int k = 0; k < 4; k++) xo[k] = ldg_bf(x + tid + k * 256);
        bo[0] = ldg_bf(b2 + tid); bo[1] = ldg_bf(b2 + tid + 256);
        float mean, den;
        ln_stats(r0, r1, mean, den);
#pragma unroll
        for (int k = 0; k < 4; k++) reinterpret_cast<float*>(xs)[2 * (i0 + k * 128) + (warp & 1)] = ln_apply(xe[k], mean, den);
        hs[tid] = make_float2(ba, ba);
        if (tid + 256 < kFc) hs[tid + 256] = make_float2(bb, bb);
    }
    asm volatile("bar.sync 1, 288;" ::: "memory");
    int s = 0, ph = 0, c = tid % kFch, rg = tid / kFch, width = kFc, stages = kF1, pitch = 768;
    uint32_t base0 = ring + rg * 4 * 768 + c * 16 + (f & 1) * 64, base1 = ring + (16 + rg * 4) * 768 + c * 16 + ((f & 1) ^ 1) * 64;
    const float2* act = xs;
#pragma unroll 1
    for (int phase = 0; phase < 2; phase++) {
        float a[2][8] = {};
#pragma unroll 1
        for (int i = 0; i < stages; i++) {
            mbar_wait(full0 + 8 * s, ph);
            if (rg < 4) {
#pragma unroll
                for (int j = 0; j < 4; j++) {
                    fma8x2(a, lds128(base0 + s * kTileBytes + j * pitch), act[i * 32 + rg * 8 + 2 * j]);
                    fma8x2(a, lds128(base1 + s * kTileBytes + j * pitch), act[i * 32 + rg * 8 + 2 * j + 1]);
                }
            }
            __syncwarp();
            if (lane == 0) mbar_arrive(empty0 + 8 * s);
            if (++s == kFStages) { s = 0; ph ^= 1; }
        }
        if (rg < 4) {
#pragma unroll
            for (int bb = 0; bb < 2; bb++)
#pragma unroll
                for (int i = 0; i < 8; i++) red[(rg * 2 + bb) * width + c * 8 + i] = a[bb][i];
        }
        asm volatile("bar.sync 2, 256;" ::: "memory");
        if (phase) break;
#pragma unroll 1
        for (int i = tid; i < 2 * kFc; i += 256) {
            const float sum = (red[i] + red[2 * kFc + i]) + (red[4 * kFc + i] + red[6 * kFc + i]);
            float* hp = reinterpret_cast<float*>(hs) + (i < kFc ? 2 * i : 2 * (i - kFc) + 1);
            const float h = bf_round(bf_round(sum) + *hp);
            const float inner = 0.7978845608028654f * (h + 0.044715f * h * h * h);
            *hp = bf_round(0.5f * h * (1.f + tanhf(inner)));
        }
        asm volatile("bar.sync 2, 256;" ::: "memory");
        c = tid & 63; rg = tid >> 6; width = kD; stages = n2; pitch = 2048; act = hs;
        base0 = ring + rg * 8192 + c * 16; base1 = base0 + 1024;
    }
    uint2 old[4];
#pragma unroll
    for (int k = 0; k < 4; k++) {
        const int i = tid + k * 256;
        word_add(&sc->ffn[i], (red[i] + red[2 * kD + i]) + (red[4 * kD + i] + red[6 * kD + i]));
        old[k] = word_count(&sc->ffn[i], 1);
    }
    uint32_t ffn[4];
    unsigned long long prev[4];
#pragma unroll
    for (int k = 0; k < 4; k++) {
        const int i = tid + k * 256;
        ffn[k] = bf_pack(bf_round(__uint_as_float(old[k].x)) + bo[k & 1], 0.f);
        prev[k] = 0;
        asm volatile("{\n.reg .pred p;\nsetp.eq.u32 p, %4, %5;\n@p atom.relaxed.gpu.global.add.u64 %0, [%1], %2;\n"
                     "@p st.relaxed.gpu.global.u64 [%3], 0;\n}"
                     : "+l"(prev[k])
                     : "l"(&sc->acc[acc_index(i)]), "l"((unsigned long long)(ffn[k] | 1) << 32), "l"(&sc->ffn[i]),
                       "r"(old[k].y), "n"(kFfnCtas - 1)
                     : "memory");
    }
#pragma unroll
    for (int k = 0; k < 4; k++) {
        const int i = tid + k * 256;
        if ((prev[k] >> 32) == kH) finish(out + i, &sc->acc[acc_index(i)], xo[k], (uint32_t)prev[k], ffn[k]);
    }
}

__global__ void __cluster_dims__(2, 1, 1) __launch_bounds__(kThreads, 1)
fused_decode_kernel(const __nv_bfloat16* __restrict__ x, const __nv_bfloat16* __restrict__ kc,
                    const __nv_bfloat16* __restrict__ vc, Scratch* sc,
                    __nv_bfloat16* __restrict__ out, const __nv_bfloat16* __restrict__ b2,
                    const __nv_bfloat16* __restrict__ b1, const __nv_bfloat16* __restrict__ w2,
                    const __grid_constant__ CUtensorMap wqmap, const __grid_constant__ CUtensorMap womap,
                    const __grid_constant__ CUtensorMap w1map) {
    extern __shared__ __align__(1024) unsigned char smem[];
    Tail* tl = reinterpret_cast<Tail*>(smem + kRingBytes);
    const uint32_t ring = smem_u32(smem);
    const uint32_t full0 = smem_u32(tl->full), empty0 = smem_u32(tl->empty);
    {
        const uint32_t tx = threadIdx.x - 32, c = blockIdx.x + (tx >> 8) * kAttCtas;
        const char* p = reinterpret_cast<const char*>(kc) + (kv_offset(c) + tx * 64);
#pragma unroll
        for (int i = 0; i < 2; i++)
            asm volatile("{\n.reg .pred p;\nsetp.lt.u32 p, %1, 128;\n@p prefetch.global.L2 [%0];\n}"
                         ::"l"(p + i * 256 * 64), "r"(c) : "memory");
    }
    const uint32_t rank = blockIdx.x & 1, off = kv_offset(blockIdx.x);
    const int b = off >> 27, h = (off >> 22) & 31;
    const char* ksrc = reinterpret_cast<const char*>(kc) + off;
    uint64_t pol;
    asm volatile("createpolicy.fractional.L2::evict_first.b64 %0, 1.0;" : "=l"(pol));
    if (threadIdx.x == 0 && blockIdx.x < kAttCtas) {
#pragma unroll
        for (int s = 2; s < 4; s++) {
            mbar_init(full0 + 8 * s, 1);
            asm volatile("fence.mbarrier_init.release.cluster;" ::: "memory");
            mbar_expect(full0 + 8 * s, kTileBytes);
            bulk_load(ring + s * kTileBytes, ksrc + (s - 2) * kTileBytes, kTileBytes, full0 + 8 * s, pol);
        }
    }
    int tid = threadIdx.x < 32 ? threadIdx.x + 256 : threadIdx.x < 288 ? threadIdx.x - 32 : threadIdx.x;
    asm volatile("" : "+r"(tid));
    const int warp = __shfl_sync(0xFFFFFFFFu, tid >> 5, 0), lane = tid & 31;
    if (blockIdx.x >= kAttCtas) {
        ffn_cta(smem, blockIdx.x - kAttCtas, x, &w1map, b1, w2, b2, out, sc);
        return;
    }

    if (warp == 8) {
        uint32_t t_start = 0;
        if (lane == 0) {
#pragma unroll
            for (int s = 0; s < kSlots; s++)
                if (s < 2 || s >= 4) mbar_init(full0 + 8 * s, 1);
            asm volatile("fence.mbarrier_init.release.cluster;" ::: "memory");
#pragma unroll
            for (int i = 0; i < 2; i++) {
                const int s = i ^ b;
                mbar_expect(full0 + 8 * s, kTileBytes);
                tensor_load(ring + s * kTileBytes, &wqmap, h * kDh, rank * 256 + s * 128, full0 + 8 * s);
            }
            t_start = timer_ns();
#pragma unroll
            for (int s = 0; s < kSlots; s++) mbar_init(empty0 + 8 * s, 8);
#pragma unroll
            for (int s = 0; s < kSplit * 4; s++) mbar_init(smem_u32(&tl->last[s]), 1);
#pragma unroll
            for (int s = 0; s < kSplit * 4; s++) mbar_expect(smem_u32(&tl->last[s]), kPiece);
            mbar_init(smem_u32(&tl->xq), 1);
            mbar_init(smem_u32(&tl->xml), 1);
            mbar_init(smem_u32(&tl->vq), 1);
            mbar_init(smem_u32(&tl->vo), 1);
            mbar_init(smem_u32(&tl->xo), 1);
            mbar_expect(smem_u32(&tl->xq), 128 * 4);
            mbar_expect(smem_u32(&tl->xml), 16 * 8);
            mbar_expect(smem_u32(&tl->xo), 128 * 4);
            asm volatile("fence.mbarrier_init.release.cluster;" ::: "memory");
        }
        __syncwarp();
        asm volatile("barrier.cluster.arrive.relaxed.aligned;" ::: "memory");
        asm volatile("barrier.cluster.wait.aligned;" ::: "memory");
        if (lane == 0) {
            int s = 4, ph = 1;
            const char* src = ksrc + 2 * kTileBytes;
#pragma unroll 1
            for (int n = 4; n < kChunks - 2; n++) {
                const int m = n < 8 ? (n - kInFlight) ^ 2 : n - kInFlight;
                mbar_wait(full0 + 8 * (m % kSlots), (m / kSlots) & 1);
                mbar_wait(empty0 + 8 * s, ph);
                if (n == 2 + kNT) {
                    src = reinterpret_cast<const char*>(vc) + off;
                    asm volatile("prefetch.tensormap [%0];" ::"l"(&womap) : "memory");
                }
                const uint32_t dst = ring + s * kTileBytes;
                wait_until(t_start + n * kPeriod - kLead);
                if (n < kChunks - kSplit) {
                    mbar_expect(full0 + 8 * s, kTileBytes);
                    bulk_load(dst, src, kTileBytes, full0 + 8 * s, pol);
                } else {
                    const uint32_t bar = smem_u32(&tl->last[(n - kChunks + kSplit) * 4]);
#pragma unroll
                    for (int u = 0; u < 4; u++) bulk_load(dst + u * kPiece, src + u * kPiece, kPiece, bar + 8 * u, pol);
                }
                src += kTileBytes;
                if (++s == kSlots) { s = 0; ph ^= 1; }
            }
            const uint32_t due = t_start + kWoTime - ((h * 11) & 31) * kWoStagger / 32;
#pragma unroll
            for (int c = 0; c < 2; c++) {
                mbar_wait(empty0 + 8 * (kWoSlot + c), (((kChunks - 2) / kSlots) & 1) ^ 1);
#pragma unroll
                for (int i = 0; i < 4; i++) {
                    const int u = i ^ (2 * b);
                    wait_until(due + (c * 4 + i) * kWoGap);
                    tensor_load(ring + (kWoSlot + c) * kTileBytes + u * kPiece, &womap, rank * 256 + u * 64, h * kDh + c * 64,
                                smem_u32(&tl->last[(kSplit - 2 + c) * 4 + u]));
                }
            }
        }
        return;
    }
    if (warp == 9) {
        asm volatile("barrier.cluster.arrive.relaxed.aligned;" ::: "memory");
        const uint32_t psrc = smem_u32(&tl->part[0][lane * 4]);
        const uint32_t rdst = mapa(psrc + 4096, rank ^ 1);
        uint32_t rbar = mapa(smem_u32(&tl->xq), rank ^ 1), lbar = smem_u32(&tl->xq);
        uint32_t vdst = smem_u32(&tl->vec[lane * 4]), vstep = 4;
        asm volatile("barrier.cluster.wait.aligned;" ::: "memory");
#pragma unroll 1
        for (int which = 0; which < 2; which++) {
            asm volatile("bar.sync 2, 288;" ::: "memory");
            uint4 v[8];
#pragma unroll
            for (int i = 0; i < 8; i++) v[i] = lds128(psrc + i * 512);
#define SUM8(c) (((__uint_as_float(v[0].c) + __uint_as_float(v[1].c)) + (__uint_as_float(v[2].c) + __uint_as_float(v[3].c))) + \
                 ((__uint_as_float(v[4].c) + __uint_as_float(v[5].c)) + (__uint_as_float(v[6].c) + __uint_as_float(v[7].c))))
            const float m0 = SUM8(x), m1 = SUM8(y), m2 = SUM8(z), m3 = SUM8(w);
#undef SUM8
            asm volatile("st.async.shared::cluster.mbarrier::complete_tx::bytes.v4.f32 [%0], {%1, %2, %3, %4}, [%5];"
                         ::"r"(rdst), "f"(m0), "f"(m1), "f"(m2), "f"(m3), "r"(rbar) : "memory");
            mbar_wait(lbar, 0);
            const uint4 o = lds128(psrc + 4096);
            const uint32_t w0 = bf_pack(m1 + __uint_as_float(o.y), m0 + __uint_as_float(o.x));
            const uint32_t w1 = bf_pack(m3 + __uint_as_float(o.w), m2 + __uint_as_float(o.z));
            asm volatile("st.shared.u32 [%0], %1;" ::"r"(vdst), "r"(w0) : "memory");
            asm volatile("st.shared.u32 [%0], %1;" ::"r"(vdst + vstep), "r"(w1) : "memory");
            __syncwarp();
            if (lane == 0) mbar_arrive(lbar + 16);
            rbar += 8; lbar += 8; vstep = 16;
            vdst = smem_u32(tl->vec) + (lane >> 3) * 64 + (lane & 1) * 32 + ((lane >> 1) & 3) * 4;
        }
        return;
    }

    asm volatile("barrier.cluster.arrive.relaxed.aligned;" ::: "memory");
    const int g = lane >> 2, t = lane & 3;
    const __nv_bfloat16* xb = x + b * kD;
    const uint4 xr0 = ldg128(xb + lane * 8), xr1 = ldg128(xb + 256 + lane * 8);
    const float xe = ldg_bf(xb + rank * 256 + (lane >> 4) * 128 + warp * 16 + (lane & 15));
    const int ocol = rank * 256 + warp * 32 + t * 8 + g;
    const float xo = ldg_bf(xb + ocol);

    int s = 0, ph = 0, n = 0;
    auto chunk_wait = [&]() {
        const bool fin = n >= kChunks - kSplit;
        mbar_wait(fin ? smem_u32(&tl->last[(n - kChunks + kSplit) * 4 + (warp >> 1)]) : full0 + 8 * s, fin ? 0 : ph);
    };
    auto chunk_done = [&]() {
        __syncwarp();
        if (lane == 0) mbar_arrive(empty0 + 8 * s);
        n++;
        if (++s == kSlots) { s = 0; ph ^= 1; }
    };
    float acc[4][4];
    uint32_t mult = (g >> 1) == t ? (1u << ((g & 1) * 16)) : 0u;
    uint32_t va[4];
#pragma unroll
    for (int j = 0; j < 4; j++) va[j] = ring + (warp * 16 + t * 4) * 256 + (g >> 2) * 128 + (t ^ j) * 32 + (g & 3) * 8;
    asm volatile("" : "+r"(mult), "+r"(va[0]), "+r"(va[1]), "+r"(va[2]), "+r"(va[3]));
    const uint32_t pa0 = smem_u32(&tl->ps[warp][t * 4]);
    uint4 pw = make_uint4(0, 0, 0, 0);
    auto wsum_tile = [&](int i) {
        uint32_t bw[4] = {pw.x * mult, pw.y * mult, pw.z * mult, pw.w * mult};
        asm volatile("" : "+r"(bw[0]), "+r"(bw[1]), "+r"(bw[2]), "+r"(bw[3]));
        chunk_wait();
        uint2 v[4][4];
#pragma unroll
        for (int r = 0; r < 4; r += 2)
#pragma unroll
            for (int j = 0; j < 4; j++) {
                v[r][j] = lds64(va[j] + s * kTileBytes + r * 256);
                v[r + 1][j] = lds64(va[j] + s * kTileBytes + r * 256 + 256);
            }
        pw = lds128(pa0 + ((i + 1) & (kNT - 1)) * 64);
#pragma unroll
        for (int r = 0; r < 4; r += 2)
#pragma unroll
            for (int j = 0; j < 4; j++) mma16816(acc[j], v[r][j].x, v[r][j].y, v[r + 1][j].x, v[r + 1][j].y, bw[r], bw[r + 1]);
        chunk_done();
    };
    auto quad_reduce = [&](float (&o4)[4]) {
#pragma unroll
        for (int i = 0; i < 4; i++)
            o4[i] = (acc[0][i] + __shfl_xor_sync(0xFFFFFFFFu, acc[1][i], 1)) +
                    (__shfl_xor_sync(0xFFFFFFFFu, acc[2][i], 2) + __shfl_xor_sync(0xFFFFFFFFu, acc[3][i], 3));
    };
    uint32_t pdst = smem_u32(&tl->part[warp][64 * (g >> 2) + 16 * t + 4 * (g & 3)]);
    asm volatile("" : "+r"(pdst));
    auto hand_over = [&]() {
        float o4[4];
        quad_reduce(o4);
        asm volatile("st.shared.v4.f32 [%0], {%1, %2, %3, %4};" ::"r"(pdst), "f"(o4[0]), "f"(o4[1]), "f"(o4[2]), "f"(o4[3]) : "memory");
        asm volatile("bar.arrive 2, 288;" ::: "memory");
    };

    uint2 qb[4];
    {
        float mean, den;
        ln_stats(xr0, xr1, mean, den);
        tl->ps[warp][lane] = bf_bits(ln_apply(xe, mean, den));
        asm volatile("barrier.cluster.wait.aligned;" ::: "memory");
        __syncwarp();
        pw = lds128(pa0);
#pragma unroll
        for (int i = 0; i < 16; i++) (&acc[0][0])[i] = 0.f;
#pragma unroll 1
        for (int i = 0; i < 2; i++) wsum_tile(i);
        hand_over();
        mbar_wait(smem_u32(&tl->vq), 0);
#pragma unroll
        for (int j = 0; j < 4; j++) {
            const uint4 w = lds128(smem_u32(tl->vec) + (4 * (j ^ ((g >> 1) & 1)) + t) * 16);
            qb[j] = (g & 1) ? make_uint2(w.y, w.w) : make_uint2(w.x, w.z);
        }
    }

    {
        const uint32_t a0 = ring + (warp * 16 + g) * 256 + t * 16 + (g & 1) * 64;
#pragma unroll 1
        for (int i = 0; i < kNT; i++) {
            mbar_wait(full0 + 8 * s, ph);
            uint4 kv[2][4];
#pragma unroll
            for (int j = 0; j < 4; j++) {
                const uint32_t a = (a0 ^ (j * 64)) + s * kTileBytes;
                kv[0][j] = lds128(a);
                kv[1][j] = lds128(a + 8 * 256);
            }
            float c[2][4] = {};
#pragma unroll
            for (int j = 0; j < 4; j++)
#pragma unroll
                for (int u = 0; u < 2; u++) mma16816(c[u], kv[u][j].x, kv[u][j].y, kv[u][j].z, kv[u][j].w, qb[j].x, qb[j].y);
            chunk_done();
            const float dot = (t & 2) ? c[1][0] + c[1][3] : c[0][0] + c[0][3];
            const float sc2 = bf_round(bf_round(dot) * 0.08838834764831845f);
            if ((t & 1) == (g & 1)) tl->ps[warp][i * 16 + (t >> 1) * 8 + g] = __float_as_uint(sc2);
        }
    }
    {
        __syncwarp();
        const uint32_t pa = smem_u32(&tl->ps[warp][lane * 4]);
        const uint4 s0 = lds128(pa), s1 = lds128(pa + 512);
        float sv[8] = {__uint_as_float(s0.x), __uint_as_float(s0.y), __uint_as_float(s0.z), __uint_as_float(s0.w),
                       __uint_as_float(s1.x), __uint_as_float(s1.y), __uint_as_float(s1.z), __uint_as_float(s1.w)};
        float m = sv[0];
#pragma unroll
        for (int i = 1; i < 8; i++) m = fmaxf(m, sv[i]);
        m = warp_max(m);
        float l = 0.f;
#pragma unroll
        for (int i = 0; i < 8; i++) l += __expf(sv[i] - m);
        l = warp_sum(l);
        const uint32_t xml = smem_u32(&tl->xml);
        if (lane < 2) st_async2(mapa(smem_u32(&tl->ml[rank * 8 + warp]), lane), m, l, mapa(xml, lane));
        mbar_wait(xml, 0);
        const float2 e = tl->ml[lane & 15];
        float gm = e.x;
#pragma unroll
        for (int o = 8; o; o >>= 1) gm = fmaxf(gm, __shfl_xor_sync(0xFFFFFFFFu, gm, o));
        float gl = e.y * __expf(e.x - gm);
#pragma unroll
        for (int o = 8; o; o >>= 1) gl += __shfl_xor_sync(0xFFFFFFFFu, gl, o);
        const float inv = __frcp_rn(gl);
        uint32_t pb[8];
#pragma unroll
        for (int i = 0; i < 8; i++) pb[i] = bf_bits(__expf(sv[i] - gm) * inv);
        *reinterpret_cast<uint4*>(&tl->ps[warp][lane * 4]) = make_uint4(pb[0], pb[1], pb[2], pb[3]);
        *reinterpret_cast<uint4*>(&tl->ps[warp][128 + lane * 4]) = make_uint4(pb[4], pb[5], pb[6], pb[7]);
        __syncwarp();
    }
    uint32_t oa = smem_u32(&tl->vec[t * 8]);
    unsigned long long* word = &sc->acc[acc_index(b * kD + ocol)];
    __nv_bfloat16* optr = out + b * kD + ocol;
    asm volatile("" : "+l"(word), "+l"(optr), "+r"(oa));
    uint4 wf[2][4][2];
    uint32_t wa[2];
#pragma unroll
    for (int j = 0; j < 2; j++)
        wa[j] = ring + (warp >> 1) * kPiece + ((lane >> 4) * 8 + (lane & 7)) * 128 +
                (((warp & 1) * 4 + 2 * j + ((lane >> 3) & 1)) ^ (lane & 7)) * 16;
    asm volatile("" : "+r"(wa[0]), "+r"(wa[1]));
    const uint32_t piece = smem_u32(&tl->last[(kSplit - 2) * 4 + (warp >> 1)]);
    auto wo_chunk = [&](int c) {
        mbar_wait(piece + c * 8 * 4, 0);
#pragma unroll
        for (int k = 0; k < 4; k++)
#pragma unroll
            for (int j = 0; j < 2; j++) wf[c][k][j] = ldsm_trans(wa[j] + (kWoSlot + c) * kTileBytes + k * 2048);
    };
    pw = lds128(pa0);
#pragma unroll
    for (int i = 0; i < 16; i++) (&acc[0][0])[i] = 0.f;
#pragma unroll 1
    for (int i = 0; i < kNT; i++) wsum_tile(i);
    hand_over();
    {
        float y[2][2][4] = {};
        uint4 ob[4];
        auto fetch_o = [&]() {
#pragma unroll
            for (int k = 0; k < 4; k++) ob[k] = lds128(oa + k * 64);
        };
        auto product = [&](int c) {
#pragma unroll
            for (int k = 0; k < 2; k++)
#pragma unroll
                for (int j = 0; j < 2; j++) {
                    const uint4 &w0 = wf[c][2 * k][j], &w1 = wf[c][2 * k + 1][j], &o = ob[2 * c + k];
                    mma16816(y[j][0], w0.x, w0.y, w0.z, w0.w, o.x, o.y);
                    mma16816(y[j][1], w1.x, w1.y, w1.z, w1.w, o.z, o.w);
                }
        };
        const uint32_t vo = smem_u32(&tl->vo);
        auto o_before = [&](uint32_t bar) {
            for (const uint32_t t0 = clock();; check_timeout(t0)) {
                if (__all_sync(0xFFFFFFFFu, mbar_test(vo, 0))) return true;
                if (__any_sync(0xFFFFFFFFu, mbar_test(bar, 0))) return false;
            }
        };
        if (o_before(piece)) {
            fetch_o();
            wo_chunk(0);
            product(0);
            wo_chunk(1);
        } else {
            wo_chunk(0);
            if (o_before(piece + 8 * 4)) {
                fetch_o();
                product(0);
                wo_chunk(1);
            } else {
                wo_chunk(1);
                mbar_wait(vo, 0);
                fetch_o();
                product(0);
            }
        }
        product(1);
        const float ya = (t & 1) ? y[0][0][2] + y[0][1][2] : y[0][0][0] + y[0][1][0];
        const float yb = (t & 1) ? y[1][0][2] + y[1][1][2] : y[1][0][0] + y[1][1][0];
        word_add(word, (t & 2) ? yb : ya);
        const uint2 r = word_count(word, 1);
        if ((r.y & 0xFF) == kH) finish(optr, word, xo, r.x, r.y);
    }
}

typedef CUresult (*EncodeTiled)(CUtensorMap*, CUtensorMapDataType, cuuint32_t, void*, const cuuint64_t*, const cuuint64_t*,
                                const cuuint32_t*, const cuuint32_t*, CUtensorMapInterleave, CUtensorMapSwizzle,
                                CUtensorMapL2promotion, CUtensorMapFloatOOBfill);

}

extern "C" void kernel_launch(void* const* d_in, const int* in_sizes, int n_in, void* d_out, int out_size) {
    (void)in_sizes; (void)n_in; (void)out_size;
    static EncodeTiled encode = nullptr;
    static Scratch* scratch = nullptr;
    if (!encode) {
        cudaGetSymbolAddress((void**)&scratch, g_scratch);
        cudaFuncSetAttribute(fused_decode_kernel, cudaFuncAttributeMaxDynamicSharedMemorySize, kSmemBytes);
        void* fn = nullptr;
        cudaDriverEntryPointQueryResult st;
        cudaGetDriverEntryPoint("cuTensorMapEncodeTiled", &fn, cudaEnableDefault, &st);
        encode = (EncodeTiled)fn;
    }
    CUtensorMap wqmap, womap, w1map;
    const cuuint32_t ones[2] = {1, 1};
    {
        const cuuint64_t dim[2] = {kH * kDh, kD}, stride[1] = {kH * kDh * 2};
        const cuuint32_t box[2] = {kDh, 128};
        encode(&wqmap, CU_TENSOR_MAP_DATA_TYPE_BFLOAT16, 2, d_in[3], dim, stride, box, ones, CU_TENSOR_MAP_INTERLEAVE_NONE,
               CU_TENSOR_MAP_SWIZZLE_NONE, CU_TENSOR_MAP_L2_PROMOTION_L2_256B, CU_TENSOR_MAP_FLOAT_OOB_FILL_NONE);
    }
    {
        const cuuint64_t dim[2] = {kD, kH * kDh}, stride[1] = {kD * 2};
        const cuuint32_t box[2] = {64, 64};
        encode(&womap, CU_TENSOR_MAP_DATA_TYPE_BFLOAT16, 2, d_in[4], dim, stride, box, ones, CU_TENSOR_MAP_INTERLEAVE_NONE,
               CU_TENSOR_MAP_SWIZZLE_128B, CU_TENSOR_MAP_L2_PROMOTION_L2_256B, CU_TENSOR_MAP_FLOAT_OOB_FILL_NONE);
    }
    {
        const cuuint64_t dim[2] = {kF, kD / 2}, stride[1] = {kF * 4};
        const cuuint32_t box[2] = {192, 16};
        encode(&w1map, CU_TENSOR_MAP_DATA_TYPE_UINT32, 2, d_in[6], dim, stride, box, ones, CU_TENSOR_MAP_INTERLEAVE_NONE,
               CU_TENSOR_MAP_SWIZZLE_NONE, CU_TENSOR_MAP_L2_PROMOTION_L2_256B, CU_TENSOR_MAP_FLOAT_OOB_FILL_NONE);
    }
    typedef const __nv_bfloat16* P;
    fused_decode_kernel<<<kCtas, kThreads, kSmemBytes, cudaStreamPerThread>>>(
        (P)d_in[0], (P)d_in[1], (P)d_in[2], scratch, (__nv_bfloat16*)d_out, (P)d_in[9], (P)d_in[7], (P)d_in[8],
        wqmap, womap, w1map);
}
```

```cpp
#include <cuda.h>
#include <cuda_runtime.h>
#include <cuda_bf16.h>
#include <stdint.h>

namespace {

constexpr int kD = 512, kH = 32, kDh = 128, kSk = 16384, kWin = 4096, kF = 1376;
constexpr int kAttCtas = 128, kFfnCtas = 4, kCtas = kAttCtas + kFfnCtas;
constexpr int kThreads = 320;
constexpr int kKeysPerCta = kWin / 2;
constexpr int kTileBytes = 128 * 256;
constexpr int kNT = kKeysPerCta / 128;
constexpr int kSlots = 6;
constexpr int kChunks = 2 + 2 * kNT + 2;
constexpr int kInFlight = 4;
constexpr int kSplit = 4;
constexpr int kPiece = kTileBytes / 4;
constexpr int kRingBytes = kSlots * kTileBytes;
constexpr int kWoSlot = (kChunks - 2) % kSlots;
static_assert(kWoSlot + 1 < kSlots, "the two wo chunks use neighbouring slots");
constexpr int kPeriod = 1320, kLead = 2800;
constexpr int kWoTime = 43100, kWoStagger = 1000, kWoGap = 96;
constexpr uint32_t kWaitCycles = 1u << 30;

constexpr int kFc = 352;
constexpr int kFch = kFc / 8;

struct __align__(16) Tail {
    float part[8][128];
    float peer[128];
    uint32_t ps[8][256];
    unsigned short vec[128];
    float2 ml[16];
    unsigned long long full[kSlots], empty[kSlots], last[kSplit * 4], xq, xo, vq, vo, xml;
};
constexpr int kSmemBytes = kRingBytes + (int)sizeof(Tail);

struct Scratch {
    unsigned long long acc[2 * kD * 4];
    unsigned long long ffn[2 * kD];
};
__device__ __align__(128) Scratch g_scratch;

__device__ __forceinline__ uint32_t smem_u32(const void* p) { return (uint32_t)__cvta_generic_to_shared(p); }
__device__ __forceinline__ void mbar_init(uint32_t a, uint32_t c) {
    asm volatile("mbarrier.init.shared::cta.b64 [%0], %1;" ::"r"(a), "r"(c) : "memory");
}
__device__ __forceinline__ void mbar_expect(uint32_t a, uint32_t bytes) {
    asm volatile("mbarrier.arrive.expect_tx.shared::cta.b64 _, [%0], %1;" ::"r"(a), "r"(bytes) : "memory");
}
__device__ __forceinline__ void mbar_arrive(uint32_t a) {
    asm volatile("mbarrier.arrive.shared::cta.b64 _, [%0];" ::"r"(a) : "memory");
}
__device__ __forceinline__ void check_timeout(uint32_t t0) {
    if ((uint32_t)clock() - t0 > kWaitCycles) __trap();
}
__device__ __forceinline__ uint32_t timer_ns() {
    uint32_t t;
    asm volatile("mov.u32 %0, %%globaltimer_lo;" : "=r"(t));
    return t;
}
__device__ __forceinline__ void wait_until(uint32_t due) {
    for (int it = 0; it < (1 << 16) && (int)(timer_ns() - due) < 0; it++) { }
}
__device__ __forceinline__ bool mbar_try(uint32_t a, uint32_t parity) {
    uint32_t ok;
    asm volatile("{\n.reg .pred p;\nmbarrier.try_wait.parity.shared::cta.b64 p, [%1], %2;\nselp.u32 %0, 1, 0, p;\n}"
                 : "=r"(ok) : "r"(a), "r"(parity) : "memory");
    return ok;
}
__device__ __forceinline__ bool mbar_test(uint32_t a, uint32_t parity) {
    uint32_t ok;
    asm volatile("{\n.reg .pred p;\nmbarrier.test_wait.parity.shared::cta.b64 p, [%1], %2;\nselp.u32 %0, 1, 0, p;\n}"
                 : "=r"(ok) : "r"(a), "r"(parity) : "memory");
    return ok;
}
__device__ __forceinline__ void mbar_wait(uint32_t a, uint32_t parity) {
    if (mbar_try(a, parity)) return;
    const uint32_t t0 = clock();
    while (!mbar_try(a, parity)) check_timeout(t0);
}
__device__ __forceinline__ void mbar_wait_cluster(uint32_t a) {
    for (const uint32_t t0 = clock();; check_timeout(t0)) {
        uint32_t ok;
        asm volatile("{\n.reg .pred p;\nmbarrier.try_wait.parity.acquire.cluster.shared::cta.b64 p, [%1], 0;\nselp.u32 %0, 1, 0, p;\n}"
                     : "=r"(ok) : "r"(a) : "memory");
        if (ok) return;
    }
}
__device__ __forceinline__ void bulk_load(uint32_t dst, const void* src, uint32_t bytes, uint32_t bar, uint64_t pol) {
    asm volatile("cp.async.bulk.shared::cluster.global.mbarrier::complete_tx::bytes.L2::cache_hint [%0], [%1], %2, [%3], %4;"
                 ::"r"(dst), "l"(src), "r"(bytes), "r"(bar), "l"(pol) : "memory");
}
__device__ __forceinline__ void tensor_load(uint32_t dst, const CUtensorMap* map, int c0, int c1, uint32_t bar) {
    asm volatile("cp.async.bulk.tensor.2d.shared::cluster.global.mbarrier::complete_tx::bytes [%0], [%1, {%2, %3}], [%4];"
                 ::"r"(dst), "l"(map), "r"(c0), "r"(c1), "r"(bar) : "memory");
}
__device__ __forceinline__ uint32_t mapa(uint32_t a, uint32_t rank) {
    uint32_t r;
    asm("mapa.shared::cluster.u32 %0, %1, %2;" : "=r"(r) : "r"(a), "r"(rank));
    return r;
}
__device__ __forceinline__ void st_async2(uint32_t dst, float a, float b, uint32_t bar) {
    asm volatile("st.async.shared::cluster.mbarrier::complete_tx::bytes.v2.f32 [%0], {%1, %2}, [%3];"
                 ::"r"(dst), "f"(a), "f"(b), "r"(bar) : "memory");
}
__device__ __forceinline__ uint4 lds128(uint32_t a) {
    uint4 v;
    asm volatile("ld.shared.v4.u32 {%0, %1, %2, %3}, [%4];" : "=r"(v.x), "=r"(v.y), "=r"(v.z), "=r"(v.w) : "r"(a) : "memory");
    return v;
}
__device__ __forceinline__ uint4 ldg128(const void* p) {
    uint4 v;
    asm volatile("ld.global.nc.v4.u32 {%0, %1, %2, %3}, [%4];" : "=r"(v.x), "=r"(v.y), "=r"(v.z), "=r"(v.w) : "l"(p));
    return v;
}
__device__ __forceinline__ float ldg_bf(const __nv_bfloat16* p) {
    unsigned short v;
    asm volatile("ld.global.nc.u16 %0, [%1];" : "=h"(v) : "l"(p));
    return __uint_as_float((uint32_t)v << 16);
}
__device__ __forceinline__ uint2 lds64(uint32_t a) {
    uint2 v;
    asm volatile("ld.shared.v2.u32 {%0, %1}, [%2];" : "=r"(v.x), "=r"(v.y) : "r"(a) : "memory");
    return v;
}
__device__ __forceinline__ uint4 ldsm_trans(uint32_t a) {
    uint4 v;
    asm volatile("ldmatrix.sync.aligned.m8n8.x4.trans.shared.b16 {%0, %1, %2, %3}, [%4];"
                 : "=r"(v.x), "=r"(v.y), "=r"(v.z), "=r"(v.w) : "r"(a) : "memory");
    return v;
}
__device__ __forceinline__ void word_add(unsigned long long* w, float v) {
    asm volatile("red.relaxed.gpu.global.add.f32 [%0], %1;" ::"l"(w), "f"(v) : "memory");
}
__device__ __forceinline__ uint2 word_count(unsigned long long* w, uint32_t hi) {
    unsigned long long r;
    asm volatile("atom.relaxed.gpu.global.add.u64 %0, [%1], %2;" : "=l"(r) : "l"(w), "l"((unsigned long long)hi << 32) : "memory");
    return make_uint2((uint32_t)r, (uint32_t)(r >> 32));
}
__device__ __forceinline__ void word_clear(unsigned long long* w) {
    asm volatile("st.relaxed.gpu.global.u64 [%0], %1;" ::"l"(w), "l"(0ULL) : "memory");
}
__device__ __forceinline__ int acc_index(int i) { return (i >> 2) * 16 + (i & 3); }
__device__ __forceinline__ void mma16816(float (&c)[4], uint32_t a0, uint32_t a1, uint32_t a2, uint32_t a3,
                                         uint32_t b0, uint32_t b1) {
    asm volatile("mma.sync.aligned.m16n8k16.row.col.f32.bf16.bf16.f32 {%0, %1, %2, %3}, {%4, %5, %6, %7}, {%8, %9}, {%0, %1, %2, %3};"
                 : "+f"(c[0]), "+f"(c[1]), "+f"(c[2]), "+f"(c[3])
                 : "r"(a0), "r"(a1), "r"(a2), "r"(a3), "r"(b0), "r"(b1));
}
__device__ __forceinline__ uint32_t bf_pack(float hi, float lo) {
    uint32_t r;
    asm("cvt.rn.bf16x2.f32 %0, %1, %2;" : "=r"(r) : "f"(hi), "f"(lo));
    return r;
}
__device__ __forceinline__ uint32_t bf_bits(float f) { return bf_pack(0.f, f); }
__device__ __forceinline__ float bf_round(float f) { return __uint_as_float(bf_pack(f, 0.f)); }
__device__ __forceinline__ float bf_lo(uint32_t w) { return __uint_as_float(w << 16); }
__device__ __forceinline__ float bf_hi(uint32_t w) { return __uint_as_float(w & 0xFFFF0000u); }
__device__ __forceinline__ float warp_sum(float v) {
#pragma unroll
    for (int o = 16; o; o >>= 1) v += __shfl_xor_sync(0xFFFFFFFFu, v, o);
    return v;
}
__device__ __forceinline__ float warp_max(float v) {
#pragma unroll
    for (int o = 16; o; o >>= 1) v = fmaxf(v, __shfl_xor_sync(0xFFFFFFFFu, v, o));
    return v;
}

__device__ __forceinline__ void finish(__nv_bfloat16* dst, unsigned long long* w, float xv, uint32_t sum, uint32_t ffn_hi) {
    const uint32_t r = bf_bits(bf_round(xv + bf_round(__uint_as_float(sum))) + bf_hi(ffn_hi));
    asm volatile("st.global.u16 [%0], %1;" ::"l"(dst), "h"((unsigned short)r) : "memory");
    word_clear(w);
}

__device__ __forceinline__ void ln_stats(const uint4& r0, const uint4& r1, float& mean_bf, float& den_bf) {
    const uint32_t w[8] = {r0.x, r0.y, r0.z, r0.w, r1.x, r1.y, r1.z, r1.w};
    float s = 0.f;
#pragma unroll
    for (int i = 0; i < 8; i++) s += bf_lo(w[i]) + bf_hi(w[i]);
    const float mean = warp_sum(s) * (1.f / kD);
    float v = 0.f;
#pragma unroll
    for (int i = 0; i < 8; i++) {
        const float a = bf_lo(w[i]) - mean, c = bf_hi(w[i]) - mean;
        v += a * a + c * c;
    }
    const float var = warp_sum(v) * (1.f / kD);
    mean_bf = bf_round(mean);
    den_bf = bf_round(sqrtf(bf_round(bf_round(var) + 1e-5f)));
}
__device__ __forceinline__ float ln_apply(float x, float mean_bf, float den_bf) {
    return bf_round(bf_round(x - mean_bf) / den_bf);
}

__device__ __forceinline__ void fma8x2(float (&a)[2][8], const uint4& w, float2 s) {
    const uint32_t u[4] = {w.x, w.y, w.z, w.w};
#pragma unroll
    for (int i = 0; i < 4; i++) {
        const float lo = bf_lo(u[i]), hi = bf_hi(u[i]);
        a[0][2 * i] = fmaf(s.x, lo, a[0][2 * i]);
        a[0][2 * i + 1] = fmaf(s.x, hi, a[0][2 * i + 1]);
        a[1][2 * i] = fmaf(s.y, lo, a[1][2 * i]);
        a[1][2 * i + 1] = fmaf(s.y, hi, a[1][2 * i + 1]);
    }
}

__device__ __forceinline__ uint32_t kv_offset(uint32_t cta) {
    const uint32_t pair = cta >> 1;
    const uint32_t c8 = pair - 4, r7 = (pair * 37 - 36 * 37) >> 8;
    const uint32_t bh0 = ((pair & 1) << 5) + 30 + (pair >> 1);
    const uint32_t bh8 = ((c8 & 8) << 2) + (c8 & 7) + ((c8 >> 1) & 8);
    const uint32_t bh7 = ((r7 & 1) << 5) + pair - 20 - ((r7 + 1) >> 1) * 7;
    const uint32_t bh = pair < 4 ? bh0 : pair < 36 ? bh8 : bh7;
    return (bh * kSk + (kSk - kWin) + (cta & 1) * kKeysPerCta) * (kDh * 2);
}

constexpr int kFStages = kSlots - 1, kF1 = kD / 32;
__device__ __forceinline__ void ffn_cta(unsigned char* smem, int f, const __nv_bfloat16* x, const CUtensorMap* w1map,
                                        const __nv_bfloat16* b1, const __nv_bfloat16* w2,
                                        const __nv_bfloat16* b2, __nv_bfloat16* out, Scratch* sc) {
    const uint32_t ring = smem_u32(smem);
    const uint32_t full0 = ring + kRingBytes, empty0 = full0 + 64;
    float2* xs = reinterpret_cast<float2*>(smem + kFStages * kTileBytes);
    float2* hs = xs + kD;
    float* red = reinterpret_cast<float*>(hs + kFc);
    const int tid = threadIdx.x, warp = tid >> 5, lane = tid & 31;
    const int cols = min(kFc, kF - f * kFc), n2 = cols / 32;
    if (warp > 8) return;
    if (warp == 8) {
        if (lane == 0) {
            for (int s = 0; s < kFStages; s++) { mbar_init(full0 + 8 * s, 1); mbar_init(empty0 + 8 * s, 8); }
            asm volatile("fence.mbarrier_init.release.cluster;" ::: "memory");
        }
        __syncwarp();
        asm volatile("bar.arrive 1, 288;" ::: "memory");
        if (lane == 0) {
            uint64_t pol;
            asm volatile("createpolicy.fractional.L2::evict_first.b64 %0, 1.0;" : "=l"(pol));
            int s = 0, ph = 1, landed = 0;
#pragma unroll 1
            for (int i = 0; i < kF1 + n2; i++) {
                for (; landed <= i - (i < kF1 ? kFStages : kInFlight); landed++)
                    mbar_wait(full0 + 8 * (landed % kFStages), (landed / kFStages) & 1);
                mbar_wait(empty0 + 8 * s, ph);
                if (i < kF1) {
                    mbar_expect(full0 + 8 * s, 32 * 768);
                    tensor_load(ring + s * kTileBytes, w1map, (f * kFc / 2) & ~31, i * 16, full0 + 8 * s);
                    tensor_load(ring + s * kTileBytes + 16 * 768, w1map, ((kF + f * kFc) / 2) & ~31, i * 16, full0 + 8 * s);
                } else {
                    mbar_expect(full0 + 8 * s, kTileBytes);
                    bulk_load(ring + s * kTileBytes, w2 + (size_t)(f * kFc + (i - kF1) * 32) * kD, kTileBytes, full0 + 8 * s, pol);
                }
                if (++s == kFStages) { s = 0; ph ^= 1; }
            }
        }
        return;
    }
    float xo[4], bo[2];
    {
        const __nv_bfloat16* xb = x + (warp & 1) * kD;
        const uint4 r0 = ldg128(xb + lane * 8), r1 = ldg128(xb + 256 + lane * 8);
        const int i0 = (warp >> 1) * 32 + lane;
        float xe[4];
#pragma unroll
        for (int k = 0; k < 4; k++) xe[k] = ldg_bf(xb + i0 + k * 128);
        const float ba = ldg_bf(b1 + f * kFc + tid), bb = ldg_bf(b1 + f * kFc + min(tid + 256, cols - 1));
#pragma unroll
        for (int k = 0; k < 4; k++) xo[k] = ldg_bf(x + tid + k * 256);
        bo[0] = ldg_bf(b2 + tid); bo[1] = ldg_bf(b2 + tid + 256);
        float mean, den;
        ln_stats(r0, r1, mean, den);
#pragma unroll
        for (int k = 0; k < 4; k++) reinterpret_cast<float*>(xs)[2 * (i0 + k * 128) + (warp & 1)] = ln_apply(xe[k], mean, den);
        hs[tid] = make_float2(ba, ba);
        if (tid + 256 < kFc) hs[tid + 256] = make_float2(bb, bb);
    }
    asm volatile("bar.sync 1, 288;" ::: "memory");
    int s = 0, ph = 0, c = tid % kFch, rg = tid / kFch, width = kFc, stages = kF1, pitch = 768;
    uint32_t base0 = ring + rg * 4 * 768 + c * 16 + (f & 1) * 64, base1 = ring + (16 + rg * 4) * 768 + c * 16 + ((f & 1) ^ 1) * 64;
    const float2* act = xs;
#pragma unroll 1
    for (int phase = 0; phase < 2; phase++) {
        float a[2][8] = {};
#pragma unroll 1
        for (int i = 0; i < stages; i++) {
            mbar_wait(full0 + 8 * s, ph);
            if (rg < 4) {
#pragma unroll
                for (int j = 0; j < 4; j++) {
                    fma8x2(a, lds128(base0 + s * kTileBytes + j * pitch), act[i * 32 + rg * 8 + 2 * j]);
                    fma8x2(a, lds128(base1 + s * kTileBytes + j * pitch), act[i * 32 + rg * 8 + 2 * j + 1]);
                }
            }
            __syncwarp();
            if (lane == 0) mbar_arrive(empty0 + 8 * s);
            if (++s == kFStages) { s = 0; ph ^= 1; }
        }
        if (rg < 4) {
#pragma unroll
            for (int bb = 0; bb < 2; bb++)
#pragma unroll
                for (int i = 0; i < 8; i++) red[(rg * 2 + bb) * width + c * 8 + i] = a[bb][i];
        }
        asm volatile("bar.sync 2, 256;" ::: "memory");
        if (phase) break;
#pragma unroll 1
        for (int i = tid; i < 2 * kFc; i += 256) {
            const float sum = (red[i] + red[2 * kFc + i]) + (red[4 * kFc + i] + red[6 * kFc + i]);
            float* hp = reinterpret_cast<float*>(hs) + (i < kFc ? 2 * i : 2 * (i - kFc) + 1);
            const float h = bf_round(bf_round(sum) + *hp);
            const float inner = 0.7978845608028654f * (h + 0.044715f * h * h * h);
            *hp = bf_round(0.5f * h * (1.f + tanhf(inner)));
        }
        asm volatile("bar.sync 2, 256;" ::: "memory");
        c = tid & 63; rg = tid >> 6; width = kD; stages = n2; pitch = 2048; act = hs;
        base0 = ring + rg * 8192 + c * 16; base1 = base0 + 1024;
    }
    uint2 old[4];
#pragma unroll
    for (int k = 0; k < 4; k++) {
        const int i = tid + k * 256;
        word_add(&sc->ffn[i], (red[i] + red[2 * kD + i]) + (red[4 * kD + i] + red[6 * kD + i]));
        old[k] = word_count(&sc->ffn[i], 1);
    }
    uint32_t ffn[4];
    unsigned long long prev[4];
#pragma unroll
    for (int k = 0; k < 4; k++) {
        const int i = tid + k * 256;
        ffn[k] = bf_pack(bf_round(__uint_as_float(old[k].x)) + bo[k & 1], 0.f);
        prev[k] = 0;
        asm volatile("{\n.reg .pred p;\nsetp.eq.u32 p, %4, %5;\n@p atom.relaxed.gpu.global.add.u64 %0, [%1], %2;\n"
                     "@p st.relaxed.gpu.global.u64 [%3], 0;\n}"
                     : "+l"(prev[k])
                     : "l"(&sc->acc[acc_index(i)]), "l"((unsigned long long)(ffn[k] | 1) << 32), "l"(&sc->ffn[i]),
                       "r"(old[k].y), "n"(kFfnCtas - 1)
                     : "memory");
    }
#pragma unroll
    for (int k = 0; k < 4; k++) {
        const int i = tid + k * 256;
        if ((prev[k] >> 32) == kH) finish(out + i, &sc->acc[acc_index(i)], xo[k], (uint32_t)prev[k], ffn[k]);
    }
}

__global__ void __cluster_dims__(2, 1, 1) __launch_bounds__(kThreads, 1)
fused_decode_kernel(const __nv_bfloat16* __restrict__ x, const __nv_bfloat16* __restrict__ kc,
                    const __nv_bfloat16* __restrict__ vc, Scratch* sc,
                    __nv_bfloat16* __restrict__ out, const __nv_bfloat16* __restrict__ b2,
                    const __nv_bfloat16* __restrict__ b1, const __nv_bfloat16* __restrict__ w2,
                    const __grid_constant__ CUtensorMap wqmap, const __grid_constant__ CUtensorMap womap,
                    const __grid_constant__ CUtensorMap w1map) {
    extern __shared__ __align__(1024) unsigned char smem[];
    Tail* tl = reinterpret_cast<Tail*>(smem + kRingBytes);
    const uint32_t ring = smem_u32(smem);
    const uint32_t full0 = smem_u32(tl->full), empty0 = smem_u32(tl->empty);
    {
        const uint32_t tx = threadIdx.x - 32, c = blockIdx.x + (tx >> 8) * kAttCtas;
        const char* p = reinterpret_cast<const char*>(kc) +
                        (((c >> 1) * kSk + (kSk - kWin) + (c & 1) * kKeysPerCta) * (kDh * 2) + tx * 64);
#pragma unroll
        for (int i = 0; i < 2; i++)
            asm volatile("{\n.reg .pred p;\nsetp.lt.u32 p, %1, 128;\n@p prefetch.global.L2 [%0];\n}"
                         ::"l"(p + i * 256 * 64), "r"(c) : "memory");
    }
    const uint32_t rank = blockIdx.x & 1, off = kv_offset(blockIdx.x);
    const int b = off >> 27, h = (off >> 22) & 31;
    const char* ksrc = reinterpret_cast<const char*>(kc) + off;
    uint64_t pol;
    asm volatile("createpolicy.fractional.L2::evict_first.b64 %0, 1.0;" : "=l"(pol));
    if (threadIdx.x == 0 && blockIdx.x < kAttCtas) {
#pragma unroll
        for (int s = 2; s < 4; s++) {
            mbar_init(full0 + 8 * s, 1);
            asm volatile("fence.mbarrier_init.release.cluster;" ::: "memory");
            mbar_expect(full0 + 8 * s, kTileBytes);
            bulk_load(ring + s * kTileBytes, ksrc + (s - 2) * kTileBytes, kTileBytes, full0 + 8 * s, pol);
        }
    }
    int tid = threadIdx.x < 32 ? threadIdx.x + 256 : threadIdx.x < 288 ? threadIdx.x - 32 : threadIdx.x;
    asm volatile("" : "+r"(tid));
    const int warp = __shfl_sync(0xFFFFFFFFu, tid >> 5, 0), lane = tid & 31;
    if (blockIdx.x >= kAttCtas) {
        ffn_cta(smem, blockIdx.x - kAttCtas, x, &w1map, b1, w2, b2, out, sc);
        return;
    }

    if (warp == 8) {
        uint32_t t_start = 0;
        if (lane == 0) {
#pragma unroll
            for (int s = 0; s < kSlots; s++)
                if (s < 2 || s >= 4) mbar_init(full0 + 8 * s, 1);
            asm volatile("fence.mbarrier_init.release.cluster;" ::: "memory");
#pragma unroll
            for (int i = 0; i < 2; i++) {
                const int s = i ^ b;
                mbar_expect(full0 + 8 * s, kTileBytes);
                tensor_load(ring + s * kTileBytes, &wqmap, h * kDh, rank * 256 + s * 128, full0 + 8 * s);
            }
            t_start = timer_ns();
#pragma unroll
            for (int s = 0; s < kSlots; s++) mbar_init(empty0 + 8 * s, 8);
#pragma unroll
            for (int s = 0; s < kSplit * 4; s++) mbar_init(smem_u32(&tl->last[s]), 1);
#pragma unroll
            for (int s = 0; s < kSplit * 4; s++) mbar_expect(smem_u32(&tl->last[s]), kPiece);
            mbar_init(smem_u32(&tl->xq), 1);
            mbar_init(smem_u32(&tl->xml), 1);
            mbar_init(smem_u32(&tl->vq), 1);
            mbar_init(smem_u32(&tl->vo), 1);
            mbar_init(smem_u32(&tl->xo), 1);
            mbar_expect(smem_u32(&tl->xq), 128 * 4);
            mbar_expect(smem_u32(&tl->xml), 16 * 8);
            mbar_expect(smem_u32(&tl->xo), 128 * 4);
            asm volatile("fence.mbarrier_init.release.cluster;" ::: "memory");
        }
        __syncwarp();
        asm volatile("barrier.cluster.arrive.relaxed.aligned;" ::: "memory");
        asm volatile("barrier.cluster.wait.aligned;" ::: "memory");
        if (lane == 0) {
            int s = 4, ph = 1;
            const char* src = ksrc + 2 * kTileBytes;
#pragma unroll 1
            for (int n = 4; n < kChunks - 2; n++) {
                const int m = n < 8 ? (n - kInFlight) ^ 2 : n - kInFlight;
                mbar_wait(full0 + 8 * (m % kSlots), (m / kSlots) & 1);
                mbar_wait(empty0 + 8 * s, ph);
                if (n == 2 + kNT) {
                    src = reinterpret_cast<const char*>(vc) + off;
                    asm volatile("prefetch.tensormap [%0];" ::"l"(&womap) : "memory");
                }
                const uint32_t dst = ring + s * kTileBytes;
                wait_until(t_start + n * kPeriod - kLead);
                if (n < kChunks - kSplit) {
                    mbar_expect(full0 + 8 * s, kTileBytes);
                    bulk_load(dst, src, kTileBytes, full0 + 8 * s, pol);
                } else {
                    const uint32_t bar = smem_u32(&tl->last[(n - kChunks + kSplit) * 4]);
#pragma unroll
                    for (int u = 0; u < 4; u++) bulk_load(dst + u * kPiece, src + u * kPiece, kPiece, bar + 8 * u, pol);
                }
                src += kTileBytes;
                if (++s == kSlots) { s = 0; ph ^= 1; }
            }
            const uint32_t due = t_start + kWoTime - ((h * 11) & 31) * kWoStagger / 32;
#pragma unroll
            for (int c = 0; c < 2; c++) {
                mbar_wait(empty0 + 8 * (kWoSlot + c), (((kChunks - 2) / kSlots) & 1) ^ 1);
#pragma unroll
                for (int i = 0; i < 4; i++) {
                    const int u = i ^ (2 * b);
                    wait_until(due + (c * 4 + i) * kWoGap);
                    tensor_load(ring + (kWoSlot + c) * kTileBytes + u * kPiece, &womap, rank * 256 + u * 64, h * kDh + c * 64,
                                smem_u32(&tl->last[(kSplit - 2 + c) * 4 + u]));
                }
            }
        }
        return;
    }
    if (warp == 9) {
        asm volatile("barrier.cluster.arrive.relaxed.aligned;" ::: "memory");
        const uint32_t psrc = smem_u32(&tl->part[0][lane * 4]);
        const uint32_t rdst = mapa(psrc + 4096, rank ^ 1);
        uint32_t rbar = mapa(smem_u32(&tl->xq), rank ^ 1), lbar = smem_u32(&tl->xq);
        uint32_t vdst = smem_u32(&tl->vec[lane * 4]), vstep = 4;
        asm volatile("barrier.cluster.wait.aligned;" ::: "memory");
#pragma unroll 1
        for (int which = 0; which < 2; which++) {
            asm volatile("bar.sync 2, 288;" ::: "memory");
            uint4 v[8];
#pragma unroll
            for (int i = 0; i < 8; i++) v[i] = lds128(psrc + i * 512);
#define SUM8(c) (((__uint_as_float(v[0].c) + __uint_as_float(v[1].c)) + (__uint_as_float(v[2].c) + __uint_as_float(v[3].c))) + \
                 ((__uint_as_float(v[4].c) + __uint_as_float(v[5].c)) + (__uint_as_float(v[6].c) + __uint_as_float(v[7].c))))
            const float m0 = SUM8(x), m1 = SUM8(y), m2 = SUM8(z), m3 = SUM8(w);
#undef SUM8
            asm volatile("st.async.shared::cluster.mbarrier::complete_tx::bytes.v4.f32 [%0], {%1, %2, %3, %4}, [%5];"
                         ::"r"(rdst), "f"(m0), "f"(m1), "f"(m2), "f"(m3), "r"(rbar) : "memory");
            mbar_wait_cluster(lbar);
            const uint4 o = lds128(psrc + 4096);
            const uint32_t w0 = bf_pack(m1 + __uint_as_float(o.y), m0 + __uint_as_float(o.x));
            const uint32_t w1 = bf_pack(m3 + __uint_as_float(o.w), m2 + __uint_as_float(o.z));
            asm volatile("st.shared.u32 [%0], %1;" ::"r"(vdst), "r"(w0) : "memory");
            asm volatile("st.shared.u32 [%0], %1;" ::"r"(vdst + vstep), "r"(w1) : "memory");
            __syncwarp();
            if (lane == 0) mbar_arrive(lbar + 16);
            rbar += 8; lbar += 8; vstep = 16;
            vdst = smem_u32(tl->vec) + (lane >> 3) * 64 + (lane & 1) * 32 + ((lane >> 1) & 3) * 4;
        }
        return;
    }

    asm volatile("barrier.cluster.arrive.relaxed.aligned;" ::: "memory");
    const int g = lane >> 2, t = lane & 3;
    const __nv_bfloat16* xb = x + b * kD;
    const uint4 xr0 = ldg128(xb + lane * 8), xr1 = ldg128(xb + 256 + lane * 8);
    const float xe = ldg_bf(xb + rank * 256 + (lane >> 4) * 128 + warp * 16 + (lane & 15));
    const int ocol = rank * 256 + warp * 32 + t * 8 + g;
    const float xo = ldg_bf(xb + ocol);

    int s = 0, ph = 0, n = 0;
    auto chunk_wait = [&]() {
        const bool fin = n >= kChunks - kSplit;
        mbar_wait(fin ? smem_u32(&tl->last[(n - kChunks + kSplit) * 4 + (warp >> 1)]) : full0 + 8 * s, fin ? 0 : ph);
    };
    auto chunk_done = [&]() {
        __syncwarp();
        if (lane == 0) mbar_arrive(empty0 + 8 * s);
        n++;
        if (++s == kSlots) { s = 0; ph ^= 1; }
    };
    float acc[4][4];
    uint32_t mult = (g >> 1) == t ? (1u << ((g & 1) * 16)) : 0u;
    uint32_t va[4];
#pragma unroll
    for (int j = 0; j < 4; j++) va[j] = ring + (warp * 16 + t * 4) * 256 + (g >> 2) * 128 + (t ^ j) * 32 + (g & 3) * 8;
    asm volatile("" : "+r"(mult), "+r"(va[0]), "+r"(va[1]), "+r"(va[2]), "+r"(va[3]));
    const uint32_t pa0 = smem_u32(&tl->ps[warp][t * 4]);
    uint4 pw = make_uint4(0, 0, 0, 0);
    auto wsum_tile = [&](int i) {
        uint32_t bw[4] = {pw.x * mult, pw.y * mult, pw.z * mult, pw.w * mult};
        asm volatile("" : "+r"(bw[0]), "+r"(bw[1]), "+r"(bw[2]), "+r"(bw[3]));
        chunk_wait();
        uint2 v[4][4];
#pragma unroll
        for (int r = 0; r < 4; r += 2)
#pragma unroll
            for (int j = 0; j < 4; j++) {
                v[r][j] = lds64(va[j] + s * kTileBytes + r * 256);
                v[r + 1][j] = lds64(va[j] + s * kTileBytes + r * 256 + 256);
            }
        pw = lds128(pa0 + ((i + 1) & (kNT - 1)) * 64);
#pragma unroll
        for (int r = 0; r < 4; r += 2)
#pragma unroll
            for (int j = 0; j < 4; j++) mma16816(acc[j], v[r][j].x, v[r][j].y, v[r + 1][j].x, v[r + 1][j].y, bw[r], bw[r + 1]);
        chunk_done();
    };
    auto quad_reduce = [&](float (&o4)[4]) {
#pragma unroll
        for (int i = 0; i < 4; i++)
            o4[i] = (acc[0][i] + __shfl_xor_sync(0xFFFFFFFFu, acc[1][i], 1)) +
                    (__shfl_xor_sync(0xFFFFFFFFu, acc[2][i], 2) + __shfl_xor_sync(0xFFFFFFFFu, acc[3][i], 3));
    };
    uint32_t pdst = smem_u32(&tl->part[warp][64 * (g >> 2) + 16 * t + 4 * (g & 3)]);
    asm volatile("" : "+r"(pdst));
    auto hand_over = [&]() {
        float o4[4];
        quad_reduce(o4);
        asm volatile("st.shared.v4.f32 [%0], {%1, %2, %3, %4};" ::"r"(pdst), "f"(o4[0]), "f"(o4[1]), "f"(o4[2]), "f"(o4[3]) : "memory");
        asm volatile("bar.arrive 2, 288;" ::: "memory");
    };

    uint2 qb[4];
    {
        float mean, den;
        ln_stats(xr0, xr1, mean, den);
        tl->ps[warp][lane] = bf_bits(ln_apply(xe, mean, den));
        asm volatile("barrier.cluster.wait.aligned;" ::: "memory");
        __syncwarp();
        pw = lds128(pa0);
#pragma unroll
        for (int i = 0; i < 16; i++) (&acc[0][0])[i] = 0.f;
#pragma unroll 1
        for (int i = 0; i < 2; i++) wsum_tile(i);
        hand_over();
        mbar_wait(smem_u32(&tl->vq), 0);
#pragma unroll
        for (int j = 0; j < 4; j++) {
            const uint4 w = lds128(smem_u32(tl->vec) + (4 * (j ^ ((g >> 1) & 1)) + t) * 16);
            qb[j] = (g & 1) ? make_uint2(w.y, w.w) : make_uint2(w.x, w.z);
        }
    }

    {
        const uint32_t a0 = ring + (warp * 16 + g) * 256 + t * 16 + (g & 1) * 64;
#pragma unroll 1
        for (int i = 0; i < kNT; i++) {
            mbar_wait(full0 + 8 * s, ph);
            uint4 kv[2][4];
#pragma unroll
            for (int j = 0; j < 4; j++) {
                const uint32_t a = (a0 ^ (j * 64)) + s * kTileBytes;
                kv[0][j] = lds128(a);
                kv[1][j] = lds128(a + 8 * 256);
            }
            float c[2][4] = {};
#pragma unroll
            for (int j = 0; j < 4; j++)
#pragma unroll
                for (int u = 0; u < 2; u++) mma16816(c[u], kv[u][j].x, kv[u][j].y, kv[u][j].z, kv[u][j].w, qb[j].x, qb[j].y);
            chunk_done();
            const float dot = (t & 2) ? c[1][0] + c[1][3] : c[0][0] + c[0][3];
            const float sc2 = bf_round(bf_round(dot) * 0.08838834764831845f);
            if ((t & 1) == (g & 1)) tl->ps[warp][i * 16 + (t >> 1) * 8 + g] = __float_as_uint(sc2);
        }
    }
    {
        __syncwarp();
        const uint32_t pa = smem_u32(&tl->ps[warp][lane * 4]);
        const uint4 s0 = lds128(pa), s1 = lds128(pa + 512);
        float sv[8] = {__uint_as_float(s0.x), __uint_as_float(s0.y), __uint_as_float(s0.z), __uint_as_float(s0.w),
                       __uint_as_float(s1.x), __uint_as_float(s1.y), __uint_as_float(s1.z), __uint_as_float(s1.w)};
        float m = sv[0];
#pragma unroll
        for (int i = 1; i < 8; i++) m = fmaxf(m, sv[i]);
        m = warp_max(m);
        float l = 0.f;
#pragma unroll
        for (int i = 0; i < 8; i++) l += __expf(sv[i] - m);
        l = warp_sum(l);
        const uint32_t xml = smem_u32(&tl->xml);
        if (lane < 2) st_async2(mapa(smem_u32(&tl->ml[rank * 8 + warp]), lane), m, l, mapa(xml, lane));
        mbar_wait_cluster(xml);
        const float2 e = tl->ml[lane & 15];
        float gm = e.x;
#pragma unroll
        for (int o = 8; o; o >>= 1) gm = fmaxf(gm, __shfl_xor_sync(0xFFFFFFFFu, gm, o));
        float gl = e.y * __expf(e.x - gm);
#pragma unroll
        for (int o = 8; o; o >>= 1) gl += __shfl_xor_sync(0xFFFFFFFFu, gl, o);
        const float inv = __frcp_rn(gl);
        uint32_t pb[8];
#pragma unroll
        for (int i = 0; i < 8; i++) pb[i] = bf_bits(__expf(sv[i] - gm) * inv);
        *reinterpret_cast<uint4*>(&tl->ps[warp][lane * 4]) = make_uint4(pb[0], pb[1], pb[2], pb[3]);
        *reinterpret_cast<uint4*>(&tl->ps[warp][128 + lane * 4]) = make_uint4(pb[4], pb[5], pb[6], pb[7]);
        __syncwarp();
    }
    uint32_t oa = smem_u32(&tl->vec[t * 8]);
    unsigned long long* word = &sc->acc[acc_index(b * kD + ocol)];
    __nv_bfloat16* optr = out + b * kD + ocol;
    asm volatile("" : "+l"(word), "+l"(optr), "+r"(oa));
    uint4 wf[2][4][2];
    uint32_t wa[2];
#pragma unroll
    for (int j = 0; j < 2; j++)
        wa[j] = ring + (warp >> 1) * kPiece + ((lane >> 4) * 8 + (lane & 7)) * 128 +
                (((warp & 1) * 4 + 2 * j + ((lane >> 3) & 1)) ^ (lane & 7)) * 16;
    asm volatile("" : "+r"(wa[0]), "+r"(wa[1]));
    const uint32_t piece = smem_u32(&tl->last[(kSplit - 2) * 4 + (warp >> 1)]);
    auto wo_chunk = [&](int c) {
        mbar_wait(piece + c * 8 * 4, 0);
#pragma unroll
        for (int k = 0; k < 4; k++)
#pragma unroll
            for (int j = 0; j < 2; j++) wf[c][k][j] = ldsm_trans(wa[j] + (kWoSlot + c) * kTileBytes + k * 2048);
    };
    pw = lds128(pa0);
#pragma unroll
    for (int i = 0; i < 16; i++) (&acc[0][0])[i] = 0.f;
#pragma unroll 1
    for (int i = 0; i < kNT; i++) wsum_tile(i);
    hand_over();
    {
        float y[2][2][4] = {};
        uint4 ob[4];
        auto fetch_o = [&]() {
#pragma unroll
            for (int k = 0; k < 4; k++) ob[k] = lds128(oa + k * 64);
        };
        auto product = [&](int c) {
#pragma unroll
            for (int k = 0; k < 2; k++)
#pragma unroll
                for (int j = 0; j < 2; j++) {
                    const uint4 &w0 = wf[c][2 * k][j], &w1 = wf[c][2 * k + 1][j], &o = ob[2 * c + k];
                    mma16816(y[j][0], w0.x, w0.y, w0.z, w0.w, o.x, o.y);
                    mma16816(y[j][1], w1.x, w1.y, w1.z, w1.w, o.z, o.w);
                }
        };
        const uint32_t vo = smem_u32(&tl->vo);
        auto o_before = [&](uint32_t bar) {
            for (const uint32_t t0 = clock();; check_timeout(t0)) {
                if (__all_sync(0xFFFFFFFFu, mbar_test(vo, 0))) return true;
                if (__any_sync(0xFFFFFFFFu, mbar_test(bar, 0))) return false;
            }
        };
        if (o_before(piece)) {
            fetch_o();
            wo_chunk(0);
            product(0);
            wo_chunk(1);
        } else {
            wo_chunk(0);
            if (o_before(piece + 8 * 4)) {
                fetch_o();
                product(0);
                wo_chunk(1);
            } else {
                wo_chunk(1);
                mbar_wait(vo, 0);
                fetch_o();
                product(0);
            }
        }
        product(1);
        const float ya = (t & 1) ? y[0][0][2] + y[0][1][2] : y[0][0][0] + y[0][1][0];
        const float yb = (t & 1) ? y[1][0][2] + y[1][1][2] : y[1][0][0] + y[1][1][0];
        word_add(word, (t & 2) ? yb : ya);
        const uint2 r = word_count(word, 1);
        if ((r.y & 0xFF) == kH) finish(optr, word, xo, r.x, r.y);
    }
}

typedef CUresult (*EncodeTiled)(CUtensorMap*, CUtensorMapDataType, cuuint32_t, void*, const cuuint64_t*, const cuuint64_t*,
                                const cuuint32_t*, const cuuint32_t*, CUtensorMapInterleave, CUtensorMapSwizzle,
                                CUtensorMapL2promotion, CUtensorMapFloatOOBfill);

}

extern "C" void kernel_launch(void* const* d_in, const int* in_sizes, int n_in, void* d_out, int out_size) {
    (void)in_sizes; (void)n_in; (void)out_size;
    static EncodeTiled encode = nullptr;
    static Scratch* scratch = nullptr;
    if (!encode) {
        cudaGetSymbolAddress((void**)&scratch, g_scratch);
        cudaFuncSetAttribute(fused_decode_kernel, cudaFuncAttributeMaxDynamicSharedMemorySize, kSmemBytes);
        void* fn = nullptr;
        cudaDriverEntryPointQueryResult st;
        cudaGetDriverEntryPoint("cuTensorMapEncodeTiled", &fn, cudaEnableDefault, &st);
        encode = (EncodeTiled)fn;
    }
    CUtensorMap wqmap, womap, w1map;
    const cuuint32_t ones[2] = {1, 1};
    {
        const cuuint64_t dim[2] = {kH * kDh, kD}, stride[1] = {kH * kDh * 2};
        const cuuint32_t box[2] = {kDh, 128};
        encode(&wqmap, CU_TENSOR_MAP_DATA_TYPE_BFLOAT16, 2, d_in[3], dim, stride, box, ones, CU_TENSOR_MAP_INTERLEAVE_NONE,
               CU_TENSOR_MAP_SWIZZLE_NONE, CU_TENSOR_MAP_L2_PROMOTION_L2_256B, CU_TENSOR_MAP_FLOAT_OOB_FILL_NONE);
    }
    {
        const cuuint64_t dim[2] = {kD, kH * kDh}, stride[1] = {kD * 2};
        const cuuint32_t box[2] = {64, 64};
        encode(&womap, CU_TENSOR_MAP_DATA_TYPE_BFLOAT16, 2, d_in[4], dim, stride, box, ones, CU_TENSOR_MAP_INTERLEAVE_NONE,
               CU_TENSOR_MAP_SWIZZLE_128B, CU_TENSOR_MAP_L2_PROMOTION_L2_256B, CU_TENSOR_MAP_FLOAT_OOB_FILL_NONE);
    }
    {
        const cuuint64_t dim[2] = {kF, kD / 2}, stride[1] = {kF * 4};
        const cuuint32_t box[2] = {192, 16};
        encode(&w1map, CU_TENSOR_MAP_DATA_TYPE_UINT32, 2, d_in[6], dim, stride, box, ones, CU_TENSOR_MAP_INTERLEAVE_NONE,
               CU_TENSOR_MAP_SWIZZLE_NONE, CU_TENSOR_MAP_L2_PROMOTION_L2_256B, CU_TENSOR_MAP_FLOAT_OOB_FILL_NONE);
    }
    typedef const __nv_bfloat16* P;
    fused_decode_kernel<<<kCtas, kThreads, kSmemBytes, cudaStreamPerThread>>>(
        (P)d_in[0], (P)d_in[1], (P)d_in[2], scratch, (__nv_bfloat16*)d_out, (P)d_in[9], (P)d_in[7], (P)d_in[8],
        wqmap, womap, w1map);
}
```

```cpp
#include <cuda.h>
#include <cuda_runtime.h>
#include <cuda_bf16.h>
#include <stdint.h>

namespace {

constexpr int kD = 512, kH = 32, kDh = 128, kSk = 16384, kWin = 4096, kF = 1376;
constexpr int kAttCtas = 128, kFfnCtas = 4, kCtas = kAttCtas + kFfnCtas;
constexpr int kThreads = 320;
constexpr int kKeysPerCta = kWin / 2;
constexpr int kTileBytes = 128 * 256;
constexpr int kNT = kKeysPerCta / 128;
constexpr int kSlots = 6;
constexpr int kChunks = 2 + 2 * kNT + 2;
constexpr int kInFlight = 4;
constexpr int kSplit = 4;
constexpr int kPiece = kTileBytes / 4;
constexpr int kRingBytes = kSlots * kTileBytes;
constexpr int kWoSlot = (kChunks - 2) % kSlots;
static_assert(kWoSlot + 1 < kSlots, "the two wo chunks use neighbouring slots");
constexpr int kPeriod = 1320, kLead = 2800;
constexpr int kWoTime = 43100, kWoStagger = 1000, kWoGap = 96;
constexpr uint32_t kWaitCycles = 1u << 30;

constexpr int kFc = 352;
constexpr int kFch = kFc / 8;

struct __align__(16) Tail {
    float part[8][128];
    float peer[128];
    uint32_t ps[8][256];
    unsigned short vec[128];
    float2 ml[16];
    unsigned long long full[kSlots], empty[kSlots], last[kSplit * 4], xq, xo, vq, vo, xml;
};
constexpr int kSmemBytes = kRingBytes + (int)sizeof(Tail);

struct Scratch {
    unsigned long long acc[2 * kD * 4];
    unsigned long long ffn[2 * kD];
};
__device__ __align__(128) Scratch g_scratch;

__device__ __forceinline__ uint32_t smem_u32(const void* p) { return (uint32_t)__cvta_generic_to_shared(p); }
__device__ __forceinline__ void mbar_init(uint32_t a, uint32_t c) {
    asm volatile("mbarrier.init.shared::cta.b64 [%0], %1;" ::"r"(a), "r"(c) : "memory");
}
__device__ __forceinline__ void mbar_expect(uint32_t a, uint32_t bytes) {
    asm volatile("mbarrier.arrive.expect_tx.shared::cta.b64 _, [%0], %1;" ::"r"(a), "r"(bytes) : "memory");
}
__device__ __forceinline__ void mbar_arrive(uint32_t a) {
    asm volatile("mbarrier.arrive.shared::cta.b64 _, [%0];" ::"r"(a) : "memory");
}
__device__ __forceinline__ void check_timeout(uint32_t t0) {
    if ((uint32_t)clock() - t0 > kWaitCycles) __trap();
}
__device__ __forceinline__ uint32_t timer_ns() {
    uint32_t t;
    asm volatile("mov.u32 %0, %%globaltimer_lo;" : "=r"(t));
    return t;
}
__device__ __forceinline__ void wait_until(uint32_t due) {
    for (int it = 0; it < (1 << 16) && (int)(timer_ns() - due) < 0; it++) { }
}
__device__ __forceinline__ bool mbar_try(uint32_t a, uint32_t parity) {
    uint32_t ok;
    asm volatile("{\n.reg .pred p;\nmbarrier.try_wait.parity.shared::cta.b64 p, [%1], %2;\nselp.u32 %0, 1, 0, p;\n}"
                 : "=r"(ok) : "r"(a), "r"(parity) : "memory");
    return ok;
}
__device__ __forceinline__ bool mbar_test(uint32_t a, uint32_t parity) {
    uint32_t ok;
    asm volatile("{\n.reg .pred p;\nmbarrier.test_wait.parity.shared::cta.b64 p, [%1], %2;\nselp.u32 %0, 1, 0, p;\n}"
                 : "=r"(ok) : "r"(a), "r"(parity) : "memory");
    return ok;
}
__device__ __forceinline__ void mbar_wait(uint32_t a, uint32_t parity) {
    if (mbar_try(a, parity)) return;
    const uint32_t t0 = clock();
    while (!mbar_try(a, parity)) check_timeout(t0);
}
__device__ __forceinline__ void mbar_wait_cluster(uint32_t a) {
    for (const uint32_t t0 = clock();; check_timeout(t0)) {
        uint32_t ok;
        asm volatile("{\n.reg .pred p;\nmbarrier.try_wait.parity.acquire.cluster.shared::cta.b64 p, [%1], 0;\nselp.u32 %0, 1, 0, p;\n}"
                     : "=r"(ok) : "r"(a) : "memory");
        if (ok) return;
    }
}
__device__ __forceinline__ void bulk_load(uint32_t dst, const void* src, uint32_t bytes, uint32_t bar, uint64_t pol) {
    asm volatile("cp.async.bulk.shared::cluster.global.mbarrier::complete_tx::bytes.L2::cache_hint [%0], [%1], %2, [%3], %4;"
                 ::"r"(dst), "l"(src), "r"(bytes), "r"(bar), "l"(pol) : "memory");
}
__device__ __forceinline__ void tensor_load(uint32_t dst, const CUtensorMap* map, int c0, int c1, uint32_t bar) {
    asm volatile("cp.async.bulk.tensor.2d.shared::cluster.global.mbarrier::complete_tx::bytes [%0], [%1, {%2, %3}], [%4];"
                 ::"r"(dst), "l"(map), "r"(c0), "r"(c1), "r"(bar) : "memory");
}
__device__ __forceinline__ uint32_t mapa(uint32_t a, uint32_t rank) {
    uint32_t r;
    asm("mapa.shared::cluster.u32 %0, %1, %2;" : "=r"(r) : "r"(a), "r"(rank));
    return r;
}
__device__ __forceinline__ void st_async2(uint32_t dst, float a, float b, uint32_t bar) {
    asm volatile("st.async.shared::cluster.mbarrier::complete_tx::bytes.v2.f32 [%0], {%1, %2}, [%3];"
                 ::"r"(dst), "f"(a), "f"(b), "r"(bar) : "memory");
}
__device__ __forceinline__ uint4 lds128(uint32_t a) {
    uint4 v;
    asm volatile("ld.shared.v4.u32 {%0, %1, %2, %3}, [%4];" : "=r"(v.x), "=r"(v.y), "=r"(v.z), "=r"(v.w) : "r"(a) : "memory");
    return v;
}
__device__ __forceinline__ uint4 ldg128(const void* p) {
    uint4 v;
    asm volatile("ld.global.nc.v4.u32 {%0, %1, %2, %3}, [%4];" : "=r"(v.x), "=r"(v.y), "=r"(v.z), "=r"(v.w) : "l"(p));
    return v;
}
__device__ __forceinline__ float ldg_bf(const __nv_bfloat16* p) {
    unsigned short v;
    asm volatile("ld.global.nc.u16 %0, [%1];" : "=h"(v) : "l"(p));
    return __uint_as_float((uint32_t)v << 16);
}
__device__ __forceinline__ uint2 lds64(uint32_t a) {
    uint2 v;
    asm volatile("ld.shared.v2.u32 {%0, %1}, [%2];" : "=r"(v.x), "=r"(v.y) : "r"(a) : "memory");
    return v;
}
__device__ __forceinline__ uint4 ldsm_trans(uint32_t a) {
    uint4 v;
    asm volatile("ldmatrix.sync.aligned.m8n8.x4.trans.shared.b16 {%0, %1, %2, %3}, [%4];"
                 : "=r"(v.x), "=r"(v.y), "=r"(v.z), "=r"(v.w) : "r"(a) : "memory");
    return v;
}
__device__ __forceinline__ void word_add(unsigned long long* w, float v) {
    asm volatile("red.relaxed.gpu.global.add.f32 [%0], %1;" ::"l"(w), "f"(v) : "memory");
}
__device__ __forceinline__ uint2 word_count(unsigned long long* w, uint32_t hi) {
    unsigned long long r;
    asm volatile("atom.relaxed.gpu.global.add.u64 %0, [%1], %2;" : "=l"(r) : "l"(w), "l"((unsigned long long)hi << 32) : "memory");
    return make_uint2((uint32_t)r, (uint32_t)(r >> 32));
}
__device__ __forceinline__ void word_clear(unsigned long long* w) {
    asm volatile("st.relaxed.gpu.global.u64 [%0], %1;" ::"l"(w), "l"(0ULL) : "memory");
}
__device__ __forceinline__ int acc_index(int i) { return (i >> 2) * 16 + (i & 3); }
__device__ __forceinline__ void mma16816(float (&c)[4], uint32_t a0, uint32_t a1, uint32_t a2, uint32_t a3,
                                         uint32_t b0, uint32_t b1) {
    asm volatile("mma.sync.aligned.m16n8k16.row.col.f32.bf16.bf16.f32 {%0, %1, %2, %3}, {%4, %5, %6, %7}, {%8, %9}, {%0, %1, %2, %3};"
                 : "+f"(c[0]), "+f"(c[1]), "+f"(c[2]), "+f"(c[3])
                 : "r"(a0), "r"(a1), "r"(a2), "r"(a3), "r"(b0), "r"(b1));
}
__device__ __forceinline__ uint32_t bf_pack(float hi, float lo) {
    uint32_t r;
    asm("cvt.rn.bf16x2.f32 %0, %1, %2;" : "=r"(r) : "f"(hi), "f"(lo));
    return r;
}
__device__ __forceinline__ uint32_t bf_bits(float f) { return bf_pack(0.f, f); }
__device__ __forceinline__ float bf_round(float f) { return __uint_as_float(bf_pack(f, 0.f)); }
__device__ __forceinline__ float bf_lo(uint32_t w) { return __uint_as_float(w << 16); }
__device__ __forceinline__ float bf_hi(uint32_t w) { return __uint_as_float(w & 0xFFFF0000u); }
__device__ __forceinline__ float warp_sum(float v) {
#pragma unroll
    for (int o = 16; o; o >>= 1) v += __shfl_xor_sync(0xFFFFFFFFu, v, o);
    return v;
}
__device__ __forceinline__ float warp_max(float v) {
#pragma unroll
    for (int o = 16; o; o >>= 1) v = fmaxf(v, __shfl_xor_sync(0xFFFFFFFFu, v, o));
    return v;
}

__device__ __forceinline__ void finish(__nv_bfloat16* dst, unsigned long long* w, float xv, uint32_t sum, uint32_t ffn_hi) {
    const uint32_t r = bf_bits(bf_round(xv + bf_round(__uint_as_float(sum))) + bf_hi(ffn_hi));
    asm volatile("st.global.u16 [%0], %1;" ::"l"(dst), "h"((unsigned short)r) : "memory");
    word_clear(w);
}

__device__ __forceinline__ void ln_stats(const uint4& r0, const uint4& r1, float& mean_bf, float& den_bf) {
    const uint32_t w[8] = {r0.x, r0.y, r0.z, r0.w, r1.x, r1.y, r1.z, r1.w};
    float s = 0.f;
#pragma unroll
    for (int i = 0; i < 8; i++) s += bf_lo(w[i]) + bf_hi(w[i]);
    const float mean = warp_sum(s) * (1.f / kD);
    float v = 0.f;
#pragma unroll
    for (int i = 0; i < 8; i++) {
        const float a = bf_lo(w[i]) - mean, c = bf_hi(w[i]) - mean;
        v += a * a + c * c;
    }
    const float var = warp_sum(v) * (1.f / kD);
    mean_bf = bf_round(mean);
    den_bf = bf_round(sqrtf(bf_round(bf_round(var) + 1e-5f)));
}
__device__ __forceinline__ float ln_apply(float x, float mean_bf, float den_bf) {
    return bf_round(bf_round(x - mean_bf) / den_bf);
}

__device__ __forceinline__ void fma8x2(float (&a)[2][8], const uint4& w, float2 s) {
    const uint32_t u[4] = {w.x, w.y, w.z, w.w};
#pragma unroll
    for (int i = 0; i < 4; i++) {
        const float lo = bf_lo(u[i]), hi = bf_hi(u[i]);
        a[0][2 * i] = fmaf(s.x, lo, a[0][2 * i]);
        a[0][2 * i + 1] = fmaf(s.x, hi, a[0][2 * i + 1]);
        a[1][2 * i] = fmaf(s.y, lo, a[1][2 * i]);
        a[1][2 * i + 1] = fmaf(s.y, hi, a[1][2 * i + 1]);
    }
}

__device__ __forceinline__ uint32_t kv_offset(uint32_t cta) {
    const uint32_t pair = cta >> 1;
    const uint32_t c8 = pair - 4, r7 = (pair * 37 - 36 * 37) >> 8;
    const uint32_t bh0 = ((pair & 1) << 5) + 30 + (pair >> 1);
    const uint32_t bh8 = ((c8 & 8) << 2) + (c8 & 7) + ((c8 >> 1) & 8);
    const uint32_t bh7 = ((r7 & 1) << 5) + pair - 20 - ((r7 + 1) >> 1) * 7;
    const uint32_t bh = pair < 4 ? bh0 : pair < 36 ? bh8 : bh7;
    return (bh * kSk + (kSk - kWin) + (cta & 1) * kKeysPerCta) * (kDh * 2);
}

constexpr int kFStages = kSlots - 1, kF1 = kD / 32;
__device__ __forceinline__ void ffn_cta(unsigned char* smem, int f, const __nv_bfloat16* x, const CUtensorMap* w1map,
                                        const __nv_bfloat16* b1, const __nv_bfloat16* w2,
                                        const __nv_bfloat16* b2, __nv_bfloat16* out, Scratch* sc) {
    const uint32_t ring = smem_u32(smem);
    const uint32_t full0 = ring + kRingBytes, empty0 = full0 + 64;
    float2* xs = reinterpret_cast<float2*>(smem + kFStages * kTileBytes);
    float2* hs = xs + kD;
    float* red = reinterpret_cast<float*>(hs + kFc);
    const int tid = threadIdx.x, warp = tid >> 5, lane = tid & 31;
    const int cols = min(kFc, kF - f * kFc), n2 = cols / 32;
    if (warp > 8) return;
    if (warp == 8) {
        if (lane == 0) {
            for (int s = 0; s < kFStages; s++) { mbar_init(full0 + 8 * s, 1); mbar_init(empty0 + 8 * s, 8); }
            asm volatile("fence.mbarrier_init.release.cluster;" ::: "memory");
        }
        __syncwarp();
        asm volatile("bar.arrive 1, 288;" ::: "memory");
        if (lane == 0) {
            uint64_t pol;
            asm volatile("createpolicy.fractional.L2::evict_first.b64 %0, 1.0;" : "=l"(pol));
            int s = 0, ph = 1, landed = 0;
#pragma unroll 1
            for (int i = 0; i < kF1 + n2; i++) {
                for (; landed <= i - (i < kF1 ? kFStages : kInFlight); landed++)
                    mbar_wait(full0 + 8 * (landed % kFStages), (landed / kFStages) & 1);
                mbar_wait(empty0 + 8 * s, ph);
                if (i < kF1) {
                    mbar_expect(full0 + 8 * s, 32 * 768);
                    tensor_load(ring + s * kTileBytes, w1map, (f * kFc / 2) & ~31, i * 16, full0 + 8 * s);
                    tensor_load(ring + s * kTileBytes + 16 * 768, w1map, ((kF + f * kFc) / 2) & ~31, i * 16, full0 + 8 * s);
                } else {
                    mbar_expect(full0 + 8 * s, kTileBytes);
                    bulk_load(ring + s * kTileBytes, w2 + (size_t)(f * kFc + (i - kF1) * 32) * kD, kTileBytes, full0 + 8 * s, pol);
                }
                if (++s == kFStages) { s = 0; ph ^= 1; }
            }
        }
        return;
    }
    float xo[4], bo[2];
    {
        const __nv_bfloat16* xb = x + (warp & 1) * kD;
        const uint4 r0 = ldg128(xb + lane * 8), r1 = ldg128(xb + 256 + lane * 8);
        const int i0 = (warp >> 1) * 32 + lane;
        float xe[4];
#pragma unroll
        for (int k = 0; k < 4; k++) xe[k] = ldg_bf(xb + i0 + k * 128);
        const float ba = ldg_bf(b1 + f * kFc + tid), bb = ldg_bf(b1 + f * kFc + min(tid + 256, cols - 1));
#pragma unroll
        for (int k = 0; k < 4; k++) xo[k] = ldg_bf(x + tid + k * 256);
        bo[0] = ldg_bf(b2 + tid); bo[1] = ldg_bf(b2 + tid + 256);
        float mean, den;
        ln_stats(r0, r1, mean, den);
#pragma unroll
        for (int k = 0; k < 4; k++) reinterpret_cast<float*>(xs)[2 * (i0 + k * 128) + (warp & 1)] = ln_apply(xe[k], mean, den);
        hs[tid] = make_float2(ba, ba);
        if (tid + 256 < kFc) hs[tid + 256] = make_float2(bb, bb);
    }
    asm volatile("bar.sync 1, 288;" ::: "memory");
    int s = 0, ph = 0, c = tid % kFch, rg = tid / kFch, width = kFc, stages = kF1, pitch = 768;
    uint32_t base0 = ring + rg * 4 * 768 + c * 16 + (f & 1) * 64, base1 = ring + (16 + rg * 4) * 768 + c * 16 + ((f & 1) ^ 1) * 64;
    const float2* act = xs;
#pragma unroll 1
    for (int phase = 0; phase < 2; phase++) {
        float a[2][8] = {};
#pragma unroll 1
        for (int i = 0; i < stages; i++) {
            mbar_wait(full0 + 8 * s, ph);
            if (rg < 4) {
#pragma unroll
                for (int j = 0; j < 4; j++) {
                    fma8x2(a, lds128(base0 + s * kTileBytes + j * pitch), act[i * 32 + rg * 8 + 2 * j]);
                    fma8x2(a, lds128(base1 + s * kTileBytes + j * pitch), act[i * 32 + rg * 8 + 2 * j + 1]);
                }
            }
            __syncwarp();
            if (lane == 0) mbar_arrive(empty0 + 8 * s);
            if (++s == kFStages) { s = 0; ph ^= 1; }
        }
        if (rg < 4) {
#pragma unroll
            for (int bb = 0; bb < 2; bb++)
#pragma unroll
                for (int i = 0; i < 8; i++) red[(rg * 2 + bb) * width + c * 8 + i] = a[bb][i];
        }
        asm volatile("bar.sync 2, 256;" ::: "memory");
        if (phase) break;
#pragma unroll 1
        for (int i = tid; i < 2 * kFc; i += 256) {
            const float sum = (red[i] + red[2 * kFc + i]) + (red[4 * kFc + i] + red[6 * kFc + i]);
            float* hp = reinterpret_cast<float*>(hs) + (i < kFc ? 2 * i : 2 * (i - kFc) + 1);
            const float h = bf_round(bf_round(sum) + *hp);
            const float inner = 0.7978845608028654f * (h + 0.044715f * h * h * h);
            *hp = bf_round(0.5f * h * (1.f + tanhf(inner)));
        }
        asm volatile("bar.sync 2, 256;" ::: "memory");
        c = tid & 63; rg = tid >> 6; width = kD; stages = n2; pitch = 2048; act = hs;
        base0 = ring + rg * 8192 + c * 16; base1 = base0 + 1024;
    }
    uint2 old[4];
#pragma unroll
    for (int k = 0; k < 4; k++) {
        const int i = tid + k * 256;
        word_add(&sc->ffn[i], (red[i] + red[2 * kD + i]) + (red[4 * kD + i] + red[6 * kD + i]));
        old[k] = word_count(&sc->ffn[i], 1);
    }
    uint32_t ffn[4];
    unsigned long long prev[4];
#pragma unroll
    for (int k = 0; k < 4; k++) {
        const int i = tid + k * 256;
        ffn[k] = bf_pack(bf_round(__uint_as_float(old[k].x)) + bo[k & 1], 0.f);
        prev[k] = 0;
        asm volatile("{\n.reg .pred p;\nsetp.eq.u32 p, %4, %5;\n@p atom.relaxed.gpu.global.add.u64 %0, [%1], %2;\n"
                     "@p st.relaxed.gpu.global.u64 [%3], 0;\n}"
                     : "+l"(prev[k])
                     : "l"(&sc->acc[acc_index(i)]), "l"((unsigned long long)(ffn[k] | 1) << 32), "l"(&sc->ffn[i]),
                       "r"(old[k].y), "n"(kFfnCtas - 1)
                     : "memory");
    }
#pragma unroll
    for (int k = 0; k < 4; k++) {
        const int i = tid + k * 256;
        if ((prev[k] >> 32) == kH) finish(out + i, &sc->acc[acc_index(i)], xo[k], (uint32_t)prev[k], ffn[k]);
    }
}

__global__ void __cluster_dims__(2, 1, 1) __launch_bounds__(kThreads, 1)
fused_decode_kernel(const __nv_bfloat16* __restrict__ x, const __nv_bfloat16* __restrict__ kc,
                    const __nv_bfloat16* __restrict__ vc, Scratch* sc,
                    __nv_bfloat16* __restrict__ out, const __nv_bfloat16* __restrict__ b2,
                    const __nv_bfloat16* __restrict__ b1, const __nv_bfloat16* __restrict__ w2, uint32_t unpaced,
                    const __grid_constant__ CUtensorMap wqmap, const __grid_constant__ CUtensorMap womap,
                    const __grid_constant__ CUtensorMap w1map) {
    extern __shared__ __align__(1024) unsigned char smem[];
    Tail* tl = reinterpret_cast<Tail*>(smem + kRingBytes);
    const uint32_t ring = smem_u32(smem);
    const uint32_t full0 = smem_u32(tl->full), empty0 = smem_u32(tl->empty);
    {
        const uint32_t tx = threadIdx.x - 32, c = blockIdx.x + (tx >> 8) * kAttCtas;
        const char* p = reinterpret_cast<const char*>(kc) +
                        (((c >> 1) * kSk + (kSk - kWin) + (c & 1) * kKeysPerCta) * (kDh * 2) + tx * 64);
#pragma unroll
        for (int i = 0; i < 2; i++)
            asm volatile("{\n.reg .pred p;\nsetp.lt.u32 p, %1, 128;\n@p prefetch.global.L2 [%0];\n}"
                         ::"l"(p + i * 256 * 64), "r"(c) : "memory");
    }
    const uint32_t rank = blockIdx.x & 1, off = kv_offset(blockIdx.x);
    const int b = off >> 27, h = (off >> 22) & 31;
    const char* ksrc = reinterpret_cast<const char*>(kc) + off;
    uint64_t pol;
    asm volatile("createpolicy.fractional.L2::evict_first.b64 %0, 1.0;" : "=l"(pol));
    if (threadIdx.x == 0 && blockIdx.x < kAttCtas) {
#pragma unroll
        for (int s = 2; s < 4; s++) {
            mbar_init(full0 + 8 * s, 1);
            asm volatile("fence.mbarrier_init.release.cluster;" ::: "memory");
            mbar_expect(full0 + 8 * s, kTileBytes);
            bulk_load(ring + s * kTileBytes, ksrc + (s - 2) * kTileBytes, kTileBytes, full0 + 8 * s, pol);
        }
    }
    int tid = threadIdx.x < 32 ? threadIdx.x + 256 : threadIdx.x < 288 ? threadIdx.x - 32 : threadIdx.x;
    asm volatile("" : "+r"(tid));
    const int warp = __shfl_sync(0xFFFFFFFFu, tid >> 5, 0), lane = tid & 31;
    if (blockIdx.x >= kAttCtas) {
        ffn_cta(smem, blockIdx.x - kAttCtas, x, &w1map, b1, w2, b2, out, sc);
        return;
    }

    if (warp == 8) {
        uint32_t t_start = 0;
        if (lane == 0) {
#pragma unroll
            for (int s = 0; s < kSlots; s++)
                if (s < 2 || s >= 4) mbar_init(full0 + 8 * s, 1);
            asm volatile("fence.mbarrier_init.release.cluster;" ::: "memory");
#pragma unroll
            for (int i = 0; i < 2; i++) {
                const int s = i ^ b;
                mbar_expect(full0 + 8 * s, kTileBytes);
                tensor_load(ring + s * kTileBytes, &wqmap, h * kDh, rank * 256 + s * 128, full0 + 8 * s);
            }
            t_start = timer_ns() - unpaced;
#pragma unroll
            for (int s = 0; s < kSlots; s++) mbar_init(empty0 + 8 * s, 8);
#pragma unroll
            for (int s = 0; s < kSplit * 4; s++) mbar_init(smem_u32(&tl->last[s]), 1);
#pragma unroll
            for (int s = 0; s < kSplit * 4; s++) mbar_expect(smem_u32(&tl->last[s]), kPiece);
            mbar_init(smem_u32(&tl->xq), 1);
            mbar_init(smem_u32(&tl->xml), 1);
            mbar_init(smem_u32(&tl->vq), 1);
            mbar_init(smem_u32(&tl->vo), 1);
            mbar_init(smem_u32(&tl->xo), 1);
            mbar_expect(smem_u32(&tl->xq), 128 * 4);
            mbar_expect(smem_u32(&tl->xml), 16 * 8);
            mbar_expect(smem_u32(&tl->xo), 128 * 4);
            asm volatile("fence.mbarrier_init.release.cluster;" ::: "memory");
        }
        __syncwarp();
        asm volatile("barrier.cluster.arrive.relaxed.aligned;" ::: "memory");
        asm volatile("barrier.cluster.wait.aligned;" ::: "memory");
        if (lane == 0) {
            int s = 4, ph = 1;
            const char* src = ksrc + 2 * kTileBytes;
#pragma unroll 1
            for (int n = 4; n < kChunks - 2; n++) {
                const int m = n < 8 ? (n - kInFlight) ^ 2 : n - kInFlight;
                mbar_wait(full0 + 8 * (m % kSlots), (m / kSlots) & 1);
                mbar_wait(empty0 + 8 * s, ph);
                if (n == 2 + kNT) {
                    src = reinterpret_cast<const char*>(vc) + off;
                    asm volatile("prefetch.tensormap [%0];" ::"l"(&womap) : "memory");
                }
                const uint32_t dst = ring + s * kTileBytes;
                wait_until(t_start + n * kPeriod - kLead);
                if (n < kChunks - kSplit) {
                    mbar_expect(full0 + 8 * s, kTileBytes);
                    bulk_load(dst, src, kTileBytes, full0 + 8 * s, pol);
                } else {
                    const uint32_t bar = smem_u32(&tl->last[(n - kChunks + kSplit) * 4]);
#pragma unroll
                    for (int u = 0; u < 4; u++) bulk_load(dst + u * kPiece, src + u * kPiece, kPiece, bar + 8 * u, pol);
                }
                src += kTileBytes;
                if (++s == kSlots) { s = 0; ph ^= 1; }
            }
            const uint32_t due = t_start + kWoTime - ((h * 11) & 31) * kWoStagger / 32;
#pragma unroll
            for (int c = 0; c < 2; c++) {
                mbar_wait(empty0 + 8 * (kWoSlot + c), (((kChunks - 2) / kSlots) & 1) ^ 1);
#pragma unroll
                for (int i = 0; i < 4; i++) {
                    const int u = i ^ (2 * b);
                    wait_until(due + (c * 4 + i) * kWoGap);
                    tensor_load(ring + (kWoSlot + c) * kTileBytes + u * kPiece, &womap, rank * 256 + u * 64, h * kDh + c * 64,
                                smem_u32(&tl->last[(kSplit - 2 + c) * 4 + u]));
                }
            }
        }
        return;
    }
    if (warp == 9) {
        asm volatile("barrier.cluster.arrive.relaxed.aligned;" ::: "memory");
        const uint32_t psrc = smem_u32(&tl->part[0][lane * 4]);
        const uint32_t rdst = mapa(psrc + 4096, rank ^ 1);
        uint32_t rbar = mapa(smem_u32(&tl->xq), rank ^ 1), lbar = smem_u32(&tl->xq);
        uint32_t vdst = smem_u32(&tl->vec[lane * 4]), vstep = 4;
        asm volatile("barrier.cluster.wait.aligned;" ::: "memory");
#pragma unroll 1
        for (int which = 0; which < 2; which++) {
            asm volatile("bar.sync 2, 288;" ::: "memory");
            uint4 v[8];
#pragma unroll
            for (int i = 0; i < 8; i++) v[i] = lds128(psrc + i * 512);
#define SUM8(c) (((__uint_as_float(v[0].c) + __uint_as_float(v[1].c)) + (__uint_as_float(v[2].c) + __uint_as_float(v[3].c))) + \
                 ((__uint_as_float(v[4].c) + __uint_as_float(v[5].c)) + (__uint_as_float(v[6].c) + __uint_as_float(v[7].c))))
            const float m0 = SUM8(x), m1 = SUM8(y), m2 = SUM8(z), m3 = SUM8(w);
#undef SUM8
            asm volatile("st.async.shared::cluster.mbarrier::complete_tx::bytes.v4.f32 [%0], {%1, %2, %3, %4}, [%5];"
                         ::"r"(rdst), "f"(m0), "f"(m1), "f"(m2), "f"(m3), "r"(rbar) : "memory");
            mbar_wait_cluster(lbar);
            const uint4 o = lds128(psrc + 4096);
            const uint32_t w0 = bf_pack(m1 + __uint_as_float(o.y), m0 + __uint_as_float(o.x));
            const uint32_t w1 = bf_pack(m3 + __uint_as_float(o.w), m2 + __uint_as_float(o.z));
            asm volatile("st.shared.u32 [%0], %1;" ::"r"(vdst), "r"(w0) : "memory");
            asm volatile("st.shared.u32 [%0], %1;" ::"r"(vdst + vstep), "r"(w1) : "memory");
            __syncwarp();
            if (lane == 0) mbar_arrive(lbar + 16);
            rbar += 8; lbar += 8; vstep = 16;
            vdst = smem_u32(tl->vec) + (lane >> 3) * 64 + (lane & 1) * 32 + ((lane >> 1) & 3) * 4;
        }
        return;
    }

    asm volatile("barrier.cluster.arrive.relaxed.aligned;" ::: "memory");
    const int g = lane >> 2, t = lane & 3;
    const __nv_bfloat16* xb = x + b * kD;
    const uint4 xr0 = ldg128(xb + lane * 8), xr1 = ldg128(xb + 256 + lane * 8);
    const float xe = ldg_bf(xb + rank * 256 + (lane >> 4) * 128 + warp * 16 + (lane & 15));
    const int ocol = rank * 256 + warp * 32 + t * 8 + g;
    const float xo = ldg_bf(xb + ocol);

    int s = 0, ph = 0, n = 0;
    auto chunk_wait = [&]() {
        const bool fin = n >= kChunks - kSplit;
        mbar_wait(fin ? smem_u32(&tl->last[(n - kChunks + kSplit) * 4 + (warp >> 1)]) : full0 + 8 * s, fin ? 0 : ph);
    };
    auto chunk_done = [&]() {
        __syncwarp();
        if (lane == 0) mbar_arrive(empty0 + 8 * s);
        n++;
        if (++s == kSlots) { s = 0; ph ^= 1; }
    };
    float acc[4][4];
    uint32_t mult = (g >> 1) == t ? (1u << ((g & 1) * 16)) : 0u;
    uint32_t va[4];
#pragma unroll
    for (int j = 0; j < 4; j++) va[j] = ring + (warp * 16 + t * 4) * 256 + (g >> 2) * 128 + (t ^ j) * 32 + (g & 3) * 8;
    asm volatile("" : "+r"(mult), "+r"(va[0]), "+r"(va[1]), "+r"(va[2]), "+r"(va[3]));
    const uint32_t pa0 = smem_u32(&tl->ps[warp][t * 4]);
    uint4 pw = make_uint4(0, 0, 0, 0);
    auto wsum_tile = [&](int i) {
        uint32_t bw[4] = {pw.x * mult, pw.y * mult, pw.z * mult, pw.w * mult};
        asm volatile("" : "+r"(bw[0]), "+r"(bw[1]), "+r"(bw[2]), "+r"(bw[3]));
        chunk_wait();
        uint2 v[4][4];
#pragma unroll
        for (int r = 0; r < 4; r += 2)
#pragma unroll
            for (int j = 0; j < 4; j++) {
                v[r][j] = lds64(va[j] + s * kTileBytes + r * 256);
                v[r + 1][j] = lds64(va[j] + s * kTileBytes + r * 256 + 256);
            }
        pw = lds128(pa0 + ((i + 1) & (kNT - 1)) * 64);
#pragma unroll
        for (int r = 0; r < 4; r += 2)
#pragma unroll
            for (int j = 0; j < 4; j++) mma16816(acc[j], v[r][j].x, v[r][j].y, v[r + 1][j].x, v[r + 1][j].y, bw[r], bw[r + 1]);
        chunk_done();
    };
    auto quad_reduce = [&](float (&o4)[4]) {
#pragma unroll
        for (int i = 0; i < 4; i++)
            o4[i] = (acc[0][i] + __shfl_xor_sync(0xFFFFFFFFu, acc[1][i], 1)) +
                    (__shfl_xor_sync(0xFFFFFFFFu, acc[2][i], 2) + __shfl_xor_sync(0xFFFFFFFFu, acc[3][i], 3));
    };
    uint32_t pdst = smem_u32(&tl->part[warp][64 * (g >> 2) + 16 * t + 4 * (g & 3)]);
    asm volatile("" : "+r"(pdst));
    auto hand_over = [&]() {
        float o4[4];
        quad_reduce(o4);
        asm volatile("st.shared.v4.f32 [%0], {%1, %2, %3, %4};" ::"r"(pdst), "f"(o4[0]), "f"(o4[1]), "f"(o4[2]), "f"(o4[3]) : "memory");
        asm volatile("bar.arrive 2, 288;" ::: "memory");
    };

    uint2 qb[4];
    {
        float mean, den;
        ln_stats(xr0, xr1, mean, den);
        tl->ps[warp][lane] = bf_bits(ln_apply(xe, mean, den));
        asm volatile("barrier.cluster.wait.aligned;" ::: "memory");
        __syncwarp();
        pw = lds128(pa0);
#pragma unroll
        for (int i = 0; i < 16; i++) (&acc[0][0])[i] = 0.f;
#pragma unroll 1
        for (int i = 0; i < 2; i++) wsum_tile(i);
        hand_over();
        mbar_wait(smem_u32(&tl->vq), 0);
#pragma unroll
        for (int j = 0; j < 4; j++) {
            const uint4 w = lds128(smem_u32(tl->vec) + (4 * (j ^ ((g >> 1) & 1)) + t) * 16);
            qb[j] = (g & 1) ? make_uint2(w.y, w.w) : make_uint2(w.x, w.z);
        }
    }

    {
        const uint32_t a0 = ring + (warp * 16 + g) * 256 + t * 16 + (g & 1) * 64;
#pragma unroll 1
        for (int i = 0; i < kNT; i++) {
            mbar_wait(full0 + 8 * s, ph);
            uint4 kv[2][4];
#pragma unroll
            for (int j = 0; j < 4; j++) {
                const uint32_t a = (a0 ^ (j * 64)) + s * kTileBytes;
                kv[0][j] = lds128(a);
                kv[1][j] = lds128(a + 8 * 256);
            }
            float c[2][4] = {};
#pragma unroll
            for (int j = 0; j < 4; j++)
#pragma unroll
                for (int u = 0; u < 2; u++) mma16816(c[u], kv[u][j].x, kv[u][j].y, kv[u][j].z, kv[u][j].w, qb[j].x, qb[j].y);
            chunk_done();
            const float dot = (t & 2) ? c[1][0] + c[1][3] : c[0][0] + c[0][3];
            const float sc2 = bf_round(bf_round(dot) * 0.08838834764831845f);
            if ((t & 1) == (g & 1)) tl->ps[warp][i * 16 + (t >> 1) * 8 + g] = __float_as_uint(sc2);
        }
    }
    {
        __syncwarp();
        const uint32_t pa = smem_u32(&tl->ps[warp][lane * 4]);
        const uint4 s0 = lds128(pa), s1 = lds128(pa + 512);
        float sv[8] = {__uint_as_float(s0.x), __uint_as_float(s0.y), __uint_as_float(s0.z), __uint_as_float(s0.w),
                       __uint_as_float(s1.x), __uint_as_float(s1.y), __uint_as_float(s1.z), __uint_as_float(s1.w)};
        float m = sv[0];
#pragma unroll
        for (int i = 1; i < 8; i++) m = fmaxf(m, sv[i]);
        m = warp_max(m);
        float l = 0.f;
#pragma unroll
        for (int i = 0; i < 8; i++) l += expf(sv[i] - m);
        l = warp_sum(l);
        const uint32_t xml = smem_u32(&tl->xml);
        if (lane < 2) st_async2(mapa(smem_u32(&tl->ml[rank * 8 + warp]), lane), m, l, mapa(xml, lane));
        mbar_wait_cluster(xml);
        const float2 e = tl->ml[lane & 15];
        float gm = e.x;
#pragma unroll
        for (int o = 8; o; o >>= 1) gm = fmaxf(gm, __shfl_xor_sync(0xFFFFFFFFu, gm, o));
        float gl = e.y * expf(e.x - gm);
#pragma unroll
        for (int o = 8; o; o >>= 1) gl += __shfl_xor_sync(0xFFFFFFFFu, gl, o);
        const float inv = __frcp_rn(gl);
        uint32_t pb[8];
#pragma unroll
        for (int i = 0; i < 8; i++) pb[i] = bf_bits(expf(sv[i] - gm) * inv);
        *reinterpret_cast<uint4*>(&tl->ps[warp][lane * 4]) = make_uint4(pb[0], pb[1], pb[2], pb[3]);
        *reinterpret_cast<uint4*>(&tl->ps[warp][128 + lane * 4]) = make_uint4(pb[4], pb[5], pb[6], pb[7]);
        __syncwarp();
    }
    uint32_t oa = smem_u32(&tl->vec[t * 8]);
    unsigned long long* word = &sc->acc[acc_index(b * kD + ocol)];
    __nv_bfloat16* optr = out + b * kD + ocol;
    asm volatile("" : "+l"(word), "+l"(optr), "+r"(oa));
    uint4 wf[2][4][2];
    uint32_t wa[2];
#pragma unroll
    for (int j = 0; j < 2; j++)
        wa[j] = ring + (warp >> 1) * kPiece + ((lane >> 4) * 8 + (lane & 7)) * 128 +
                (((warp & 1) * 4 + 2 * j + ((lane >> 3) & 1)) ^ (lane & 7)) * 16;
    asm volatile("" : "+r"(wa[0]), "+r"(wa[1]));
    const uint32_t piece = smem_u32(&tl->last[(kSplit - 2) * 4 + (warp >> 1)]);
    auto wo_chunk = [&](int c) {
        mbar_wait(piece + c * 8 * 4, 0);
#pragma unroll
        for (int k = 0; k < 4; k++)
#pragma unroll
            for (int j = 0; j < 2; j++) wf[c][k][j] = ldsm_trans(wa[j] + (kWoSlot + c) * kTileBytes + k * 2048);
    };
    pw = lds128(pa0);
#pragma unroll
    for (int i = 0; i < 16; i++) (&acc[0][0])[i] = 0.f;
#pragma unroll 1
    for (int i = 0; i < kNT; i++) wsum_tile(i);
    hand_over();
    {
        float y[2][2][4] = {};
        uint4 ob[4];
        auto fetch_o = [&]() {
#pragma unroll
            for (int k = 0; k < 4; k++) ob[k] = lds128(oa + k * 64);
        };
        auto product = [&](int c) {
#pragma unroll
            for (int k = 0; k < 2; k++)
#pragma unroll
                for (int j = 0; j < 2; j++) {
                    const uint4 &w0 = wf[c][2 * k][j], &w1 = wf[c][2 * k + 1][j], &o = ob[2 * c + k];
                    mma16816(y[j][0], w0.x, w0.y, w0.z, w0.w, o.x, o.y);
                    mma16816(y[j][1], w1.x, w1.y, w1.z, w1.w, o.z, o.w);
                }
        };
        const uint32_t vo = smem_u32(&tl->vo);
        auto o_before = [&](uint32_t bar) {
            for (const uint32_t t0 = clock();; check_timeout(t0)) {
                if (__all_sync(0xFFFFFFFFu, mbar_test(vo, 0))) return true;
                if (__any_sync(0xFFFFFFFFu, mbar_test(bar, 0))) return false;
            }
        };
        if (o_before(piece)) {
            fetch_o();
            wo_chunk(0);
            product(0);
            wo_chunk(1);
        } else {
            wo_chunk(0);
            if (o_before(piece + 8 * 4)) {
                fetch_o();
                product(0);
                wo_chunk(1);
            } else {
                wo_chunk(1);
                mbar_wait(vo, 0);
                fetch_o();
                product(0);
            }
        }
        product(1);
        const float ya = (t & 1) ? y[0][0][2] + y[0][1][2] : y[0][0][0] + y[0][1][0];
        const float yb = (t & 1) ? y[1][0][2] + y[1][1][2] : y[1][0][0] + y[1][1][0];
        word_add(word, (t & 2) ? yb : ya);
        const uint2 r = word_count(word, 1);
        if ((r.y & 0xFF) == kH) finish(optr, word, xo, r.x, r.y);
    }
}

typedef CUresult (*EncodeTiled)(CUtensorMap*, CUtensorMapDataType, cuuint32_t, void*, const cuuint64_t*, const cuuint64_t*,
                                const cuuint32_t*, const cuuint32_t*, CUtensorMapInterleave, CUtensorMapSwizzle,
                                CUtensorMapL2promotion, CUtensorMapFloatOOBfill);

}

extern "C" void kernel_launch(void* const* d_in, const int* in_sizes, int n_in, void* d_out, int out_size) {
    (void)in_sizes; (void)n_in; (void)out_size;
    static EncodeTiled encode = nullptr;
    static Scratch* scratch = nullptr;
    static uint32_t unpaced = 0;
    if (!encode) {
        int dev = 0, khz = 0, bits = 0;
        cudaGetDevice(&dev);
        cudaDeviceGetAttribute(&khz, cudaDevAttrMemoryClockRate, dev);
        cudaDeviceGetAttribute(&bits, cudaDevAttrGlobalMemoryBusWidth, dev);
        if ((double)khz * bits / 4e6 > 3400.0) unpaced = 1u << 20;
        cudaGetSymbolAddress((void**)&scratch, g_scratch);
        cudaFuncSetAttribute(fused_decode_kernel, cudaFuncAttributeMaxDynamicSharedMemorySize, kSmemBytes);
        void* fn = nullptr;
        cudaDriverEntryPointQueryResult st;
        cudaGetDriverEntryPoint("cuTensorMapEncodeTiled", &fn, cudaEnableDefault, &st);
        encode = (EncodeTiled)fn;
    }
    CUtensorMap wqmap, womap, w1map;
    const cuuint32_t ones[2] = {1, 1};
    {
        const cuuint64_t dim[2] = {kH * kDh, kD}, stride[1] = {kH * kDh * 2};
        const cuuint32_t box[2] = {kDh, 128};
        encode(&wqmap, CU_TENSOR_MAP_DATA_TYPE_BFLOAT16, 2, d_in[3], dim, stride, box, ones, CU_TENSOR_MAP_INTERLEAVE_NONE,
               CU_TENSOR_MAP_SWIZZLE_NONE, CU_TENSOR_MAP_L2_PROMOTION_L2_256B, CU_TENSOR_MAP_FLOAT_OOB_FILL_NONE);
    }
    {
        const cuuint64_t dim[2] = {kD, kH * kDh}, stride[1] = {kD * 2};
        const cuuint32_t box[2] = {64, 64};
        encode(&womap, CU_TENSOR_MAP_DATA_TYPE_BFLOAT16, 2, d_in[4], dim, stride, box, ones, CU_TENSOR_MAP_INTERLEAVE_NONE,
               CU_TENSOR_MAP_SWIZZLE_128B, CU_TENSOR_MAP_L2_PROMOTION_L2_256B, CU_TENSOR_MAP_FLOAT_OOB_FILL_NONE);
    }
    {
        const cuuint64_t dim[2] = {kF, kD / 2}, stride[1] = {kF * 4};
        const cuuint32_t box[2] = {192, 16};
        encode(&w1map, CU_TENSOR_MAP_DATA_TYPE_UINT32, 2, d_in[6], dim, stride, box, ones, CU_TENSOR_MAP_INTERLEAVE_NONE,
               CU_TENSOR_MAP_SWIZZLE_NONE, CU_TENSOR_MAP_L2_PROMOTION_L2_256B, CU_TENSOR_MAP_FLOAT_OOB_FILL_NONE);
    }
    typedef const __nv_bfloat16* P;
    fused_decode_kernel<<<kCtas, kThreads, kSmemBytes, cudaStreamPerThread>>>(
        (P)d_in[0], (P)d_in[1], (P)d_in[2], scratch, (__nv_bfloat16*)d_out, (P)d_in[9], (P)d_in[7], (P)d_in[8],
        unpaced, wqmap, womap, w1map);
}
```
